```python
import torch

def _softmax(x, axis=-1):
    return torch.softmax(x, dim=axis)
def _gelu(x):
    return torch.nn.functional.gelu(x, approximate="tanh")
def _silu(x):
    return torch.nn.functional.silu(x)
def _sigmoid(x):
    return torch.sigmoid(x)
def _layernorm(x, axis=-1, eps=1e-5):
    m = x.mean(dim=axis, keepdim=True)
    v = x.var(dim=axis, keepdim=True, unbiased=False)
    return (x - m) / torch.sqrt(v + eps)
def _scatter_add(tgt, idx, src, axis=0):
    return tgt.clone().index_add_(axis, idx, src)
def _segment_sum(src, seg, n):
    out = torch.zeros((n,) + src.shape[1:], dtype=src.dtype)
    return out.index_add_(0, seg, src)
def _pad(x, pw):
    flat = tuple(v for pair in reversed(pw) for v in pair)
    return torch.nn.functional.pad(x, flat)

kernel_name = 'parallel_sum__compressed_kv_cla__moe_arch_mod__prompt'

def setup_inputs():

    _w = (lambda a: (lambda t: t.to(torch.bfloat16) if t.is_floating_point() else t)(torch.as_tensor(a)))
    def _A_setup():
        B, H, Sq, Sk, D, M = 1, 32, 2048, 2048, 128, 512
        Dc = 4 * D
        return {
            "x": _w((lambda *s: torch.randn(*s, dtype=torch.bfloat16) * 0.05)(B, Sq, M)),
            "c_kv": _w((lambda *s: torch.randn(*s, dtype=torch.bfloat16) * 1.6)(B, Sk, Dc)),
            "w_q": _w((lambda *s: torch.randn(*s, dtype=torch.bfloat16) * 1.6)(M, H, D) * (M ** -0.5)),
            "w_uk": _w((lambda *s: torch.randn(*s, dtype=torch.bfloat16) * 1.6)(Dc, H, D) * (Dc ** -0.5)),
            "w_uv": _w((lambda *s: torch.randn(*s, dtype=torch.bfloat16) * 1.6)(Dc, H, D) * (Dc ** -0.5)),
            "w_o": _w((lambda *s: torch.randn(*s, dtype=torch.bfloat16) * 1.6)(H, D, M) * ((H * D) ** -0.5)),
        }
    _A_in = _A_setup()

    def _B_setup():
        B, S, D, F, C = 1, 2048, 512, 1376, 1
        return {
            "x": _w((lambda *s: torch.randn(*s, dtype=torch.bfloat16) * 0.05)(B, S, D)),
            "w_r": _w((lambda *s: torch.randn(*s, dtype=torch.bfloat16) * 1.6)(D)),
            "w_gate": _w((lambda *s: torch.randn(*s, dtype=torch.bfloat16) * 0.1)(D, F)),
            "w_up": _w((lambda *s: torch.randn(*s, dtype=torch.bfloat16) * 0.1)(D, F)),
            "w_down": _w((lambda *s: torch.randn(*s, dtype=torch.bfloat16) * 0.1)(F, D)),
        }
    _B_in = _B_setup()

    return {
        "A_x": _A_in["x"],
        "A_c_kv": _A_in["c_kv"],
        "A_w_q": _A_in["w_q"],
        "A_w_uk": _A_in["w_uk"],
        "A_w_uv": _A_in["w_uv"],
        "A_w_o": _A_in["w_o"],
        "B_x": _B_in["x"],
        "B_w_r": _B_in["w_r"],
        "B_w_gate": _B_in["w_gate"],
        "B_w_up": _B_in["w_up"],
        "B_w_down": _B_in["w_down"],
    }

def reference(A_x, A_c_kv, A_w_q, A_w_uk, A_w_uv, A_w_o, B_x, B_w_r, B_w_gate, B_w_up, B_w_down):
    def _A_ref(x, c_kv, w_q, w_uk, w_uv, w_o):
        B, Sq, M = x.shape[0], x.shape[1], x.shape[2]
        Sk = c_kv.shape[1]
        H, D = w_q.shape[1], w_q.shape[2]
        q = torch.einsum("bqm,mhd->bhqd", x, w_q)
        k = torch.einsum("bkc,chd->bhkd", c_kv, w_uk)
        v = torch.einsum("bkc,chd->bhkd", c_kv, w_uv)
        scores = torch.einsum("bhqd,bhkd->bhqk", q, k) * (D ** -0.5)
        off = Sk - Sq
        qi = torch.arange(Sq)[:, None]
        kj = torch.arange(Sk)[None, :]
        cmask = kj <= (qi + off)
        scores = torch.where(cmask[None, None], scores, -1e9)
        p = _softmax(scores, axis=-1)
        ctx = torch.einsum("bhqk,bhkd->bhqd", p, v)
        return torch.einsum("bhqd,hdm->bqm", ctx, w_o)

    def _B_ref(x, w_r, w_gate, w_up, w_down):
        B, S, D = x.shape
        C = 1
        r = x @ w_r
        idx = torch.argsort(-r, axis=-1)[:, :C]
        idx_e = (lambda x, n, axis: torch.repeat_interleave(x, n, dim=axis))(idx.reshape(B, C, 1), D, axis=2)
        x_sel = (lambda x, i, axis: torch.take_along_dim(x, i, dim=axis))(x, idx_e, axis=1)
        g = _silu(x_sel @ w_gate)
        u = x_sel @ w_up
        y = (g * u) @ w_down
        r_sel = _sigmoid((lambda x, i, axis: torch.take_along_dim(x, i, dim=axis))(r, idx, axis=1))
        y = y * r_sel.reshape(B, C, 1)
        b_off = (torch.arange(B) * S).reshape(B, 1)
        flat_idx = (idx + b_off).reshape(B * C)
        zero = (x * 0.0).reshape(B * S, D)
        upd = _scatter_add(zero, flat_idx, y.reshape(B * C, D), axis=0)
        return x + upd.reshape(B, S, D)

    x = A_x
    xn = _layernorm(x, axis=-1)
    return x + _A_ref(xn, A_c_kv, A_w_q, A_w_uk, A_w_uv, A_w_o) + _B_ref(xn, B_w_r, B_w_gate, B_w_up, B_w_down)
```

```cpp
#include <cuda_runtime.h>
#include <cuda_bf16.h>
#include <cuda.h>
#include <stdint.h>
#include <type_traits>

typedef __nv_bfloat16 bf16;

constexpr int SEQ = 2048, DM = 512, NH = 32, FF = 1376;
constexpr int TILE = 32768;
constexpr int NSLOT = 7;
constexpr int SMEM_BYTES = NSLOT * TILE + 1024 + 640;
#define PV_A 2
#define PV_B 5
#define PF_STEP 12
#define TL_STEPS 0
constexpr int NSTEP = 17;

__device__ __align__(1024) uint8_t g_q[NH * 16 * TILE];
__device__ __align__(1024) uint8_t g_k[16 * 16 * TILE];
__device__ __align__(1024) uint8_t g_v[16 * 16 * TILE];
__device__ __align__(1024) bf16 g_xn[SEQ * DM];
__device__ unsigned long long g_key[4];
__device__ uint4 g_part[128 * 8 * 8 * 32];
__device__ float g_ypart[4 * DM];
__device__ float g_sel[4 * 2];
__device__ unsigned g_fp[3 * NH * 16], g_fc[NH * 16];
__device__ unsigned g_fln[256], g_fw[128], g_fy[8];
__device__ unsigned g_epoch[132];

struct Params {
  const bf16 *x, *w_r, *w_gate, *w_up, *w_down;
  const uint8_t *c, *wq, *wuk, *wuv, *wo;
  bf16* out;
  uint32_t zero;
};

__device__ __forceinline__ uint32_t smem_u32(const void* p) { return (uint32_t)__cvta_generic_to_shared(p); }
__device__ __forceinline__ void mbar_init(uint32_t bar, uint32_t cnt) {
  asm volatile("mbarrier.init.shared::cta.b64 [%0], %1;" ::"r"(bar), "r"(cnt) : "memory");
}
__device__ __forceinline__ void mbar_arrive(uint32_t bar) {
  asm volatile("mbarrier.arrive.shared::cta.b64 _, [%0];" ::"r"(bar) : "memory");
}
__device__ __forceinline__ void mbar_arrive_lt(uint32_t bar, uint32_t i, uint32_t n) {
  asm volatile("{\n.reg .pred p;\nsetp.lt.u32 p, %1, %2;\n@p mbarrier.arrive.shared::cta.b64 _, [%0];\n}\n" ::"r"(bar), "r"(i), "r"(n) : "memory");
}
__device__ __forceinline__ void mbar_arrive_cluster_lt(uint32_t addr, uint32_t i, uint32_t n) {
  asm volatile("{\n.reg .pred p;\nsetp.lt.u32 p, %1, %2;\n@p mbarrier.arrive.shared::cluster.b64 _, [%0];\n}\n" ::"r"(addr), "r"(i), "r"(n) : "memory");
}
__device__ __forceinline__ bool mbar_try(uint32_t bar, uint32_t parity) {
  uint32_t ok;
  asm volatile("{\n.reg .pred p;\nmbarrier.try_wait.parity.shared::cta.b64 p, [%1], %2, %3;\nselp.u32 %0, 1, 0, p;\n}\n"
               : "=r"(ok) : "r"(bar), "r"(parity), "r"(1000000) : "memory");
  return ok;
}
__device__ __forceinline__ bool mbar_test(uint32_t bar, uint32_t parity) {
  uint32_t ok;
  asm volatile("{\n.reg .pred p;\nmbarrier.test_wait.parity.shared::cta.b64 p, [%1], %2;\nselp.u32 %0, 1, 0, p;\n}\n"
               : "=r"(ok) : "r"(bar), "r"(parity) : "memory");
  return ok;
}
__device__ __forceinline__ uint32_t clk32() { uint32_t c; asm volatile("mov.u32 %0, %%clock;" : "=r"(c)); return c; }
constexpr uint32_t WAIT_LIMIT = 3000000000u;
__device__ __forceinline__ void mbar_wait(uint32_t bar, uint32_t parity) {
  if (mbar_try(bar, parity)) return;
  uint32_t t0 = clk32();
  while (!mbar_try(bar, parity))
    if (clk32() - t0 > WAIT_LIMIT) __trap();
}
__device__ __forceinline__ void mbar_spin(uint32_t bar, uint32_t parity) {
  asm volatile("{\n.reg .pred p;\nW: mbarrier.try_wait.parity.shared::cta.b64 p, [%0], %1;\n@!p bra W;\n}\n"
               ::"r"(bar), "r"(parity) : "memory");
}
__device__ __forceinline__ unsigned ld_acquire(const unsigned* p) {
  unsigned v;
  asm volatile("ld.acquire.gpu.global.u32 %0, [%1];" : "=r"(v) : "l"(p) : "memory");
  return v;
}
__device__ __forceinline__ void flag_wait(const unsigned* p, unsigned ep, unsigned ns = 40) {
  if (ld_acquire(p) == ep) return;
  uint32_t t0 = clk32();
  while (ld_acquire(p) != ep) {
    __nanosleep(ns);
    if (clk32() - t0 > WAIT_LIMIT) __trap();
  }
}
__device__ __forceinline__ void flag_set(unsigned* p, unsigned ep) {
  asm volatile("fence.acq_rel.gpu;" ::: "memory");
  asm volatile("fence.proxy.async.global;" ::: "memory");
  asm volatile("st.relaxed.gpu.global.u32 [%0], %1;" ::"l"(p), "r"(ep) : "memory");
}
__device__ __forceinline__ void fence_async_global() { asm volatile("fence.proxy.async.global;" ::: "memory"); }
#define FILL_HEAD "{\n.reg .pred p;\nelect.sync _|p, 0xffffffff;\n@p mbarrier.arrive.expect_tx.shared::cta.b64 _, [%2], 32768;\n@p "
__device__ __forceinline__ void fill_bulk(uint32_t dst, const void* src, uint32_t bar) {
  asm volatile(FILL_HEAD "cp.async.bulk.shared::cluster.global.mbarrier::complete_tx::bytes [%0], [%1], 32768, [%2];\n}\n"
               ::"r"(dst), "l"(src), "r"(bar) : "memory");
}
__device__ __forceinline__ void fill_bulk_mc(uint32_t dst, const void* src, uint32_t bar) {
  asm volatile(FILL_HEAD "cp.async.bulk.shared::cluster.global.mbarrier::complete_tx::bytes.multicast::cluster [%0], [%1], 16384, [%2], %3;\n}\n"
               ::"r"(dst), "l"(src), "r"(bar), "h"((uint16_t)3) : "memory");
}
__device__ __forceinline__ void fill_2d_mc(uint32_t dst, const CUtensorMap* tm, uint32_t bar, int c0, int c1) {
  asm volatile(FILL_HEAD "cp.async.bulk.tensor.2d.shared::cluster.global.mbarrier::complete_tx::bytes.multicast::cluster [%0], [%1, {%3, %4}], [%2], %5;\n}\n"
               ::"r"(dst), "l"(tm), "r"(bar), "r"(c0), "r"(c1), "h"((uint16_t)3) : "memory");
}
__device__ __forceinline__ void fill_3d(uint32_t dst, const CUtensorMap* tm, uint32_t bar, int c1, int c2) {
  asm volatile(FILL_HEAD "cp.async.bulk.tensor.3d.shared::cluster.global.mbarrier::complete_tx::bytes [%0], [%1, {%5, %3, %4}], [%2];\n}\n"
               ::"r"(dst), "l"(tm), "r"(bar), "r"(c1), "r"(c2), "r"(0) : "memory");
}
__device__ __forceinline__ void prefetch_l2(const void* p, uint32_t bytes) {
  asm volatile("cp.async.bulk.prefetch.L2.global [%0], %1;" ::"l"(p), "r"(bytes) : "memory");
}
__device__ __forceinline__ void wg_fence() { asm volatile("wgmma.fence.sync.aligned;" ::: "memory"); }
__device__ __forceinline__ void wg_commit() { asm volatile("wgmma.commit_group.sync.aligned;" ::: "memory"); }
template <int N> __device__ __forceinline__ void wg_wait() { asm volatile("wgmma.wait_group.sync.aligned %0;" ::"n"(N) : "memory"); }
__device__ __forceinline__ void bar_sync(int id, int n) { asm volatile("bar.sync %0, %1;" ::"r"(id), "r"(n) : "memory"); }
__device__ __forceinline__ void bar_arrive(int id, int n) { asm volatile("bar.arrive %0, %1;" ::"r"(id), "r"(n) : "memory"); }
__device__ __forceinline__ void ldsm4(uint32_t addr, uint32_t& r0, uint32_t& r1, uint32_t& r2, uint32_t& r3) {
  asm volatile("ldmatrix.sync.aligned.m8n8.x4.shared.b16 {%0,%1,%2,%3}, [%4];"
               : "=r"(r0), "=r"(r1), "=r"(r2), "=r"(r3) : "r"(addr) : "memory");
}
__device__ __forceinline__ uint32_t pack2(float lo, float hi) {
  uint32_t r;
  asm("cvt.rn.bf16x2.f32 %0, %1, %2;" : "=r"(r) : "f"(hi), "f"(lo));
  return r;
}
__device__ __forceinline__ float ex2(float x) { float y; asm("ex2.approx.ftz.f32 %0, %1;" : "=f"(y) : "f"(x)); return y; }
__device__ __forceinline__ float bf_lo(uint32_t v) { return __uint_as_float(v << 16); }
__device__ __forceinline__ float bf_hi(uint32_t v) { return __uint_as_float(v & 0xffff0000u); }
__device__ __forceinline__ float rbf(float x) { return __bfloat162float(__float2bfloat16_rn(x)); }
template <int N> __device__ __forceinline__ void pin(float (&d)[N]) {
#pragma unroll
  for (int i = 0; i < N; i++) asm volatile("" : "+f"(d[i])::"memory");
}
template <int N> __device__ __forceinline__ void pin(uint32_t (&d)[N]) {
#pragma unroll
  for (int i = 0; i < N; i++) asm volatile("" : "+r"(d[i])::"memory");
}

__device__ __forceinline__ uint64_t desc(uint32_t lo, uint32_t hi) { return ((uint64_t)hi << 32) | lo; }
constexpr uint32_t DK_LO = 1 << 16, DK_HI = (2048 >> 4) | (2u << 30);
__device__ __forceinline__ constexpr uint32_t dk_step(int k) { return ((k >> 1) * 512 + (k & 1) * 32) >> 4; }
constexpr uint32_t DN_LO = (512 >> 4) << 16, DN_HI = (2048 >> 4) | (2u << 30), DN_STEP = 4096 >> 4;
constexpr uint32_t DW_LO = (16384 >> 4) << 16, DW_HI = (1024 >> 4) | (1u << 30), DW_STEP = 2048 >> 4;

#define R8(a, i) "+f"(a[i]), "+f"(a[i + 1]), "+f"(a[i + 2]), "+f"(a[i + 3]), "+f"(a[i + 4]), "+f"(a[i + 5]), "+f"(a[i + 6]), "+f"(a[i + 7])
#define R64(a) R8(a, 0), R8(a, 8), R8(a, 16), R8(a, 24), R8(a, 32), R8(a, 40), R8(a, 48), R8(a, 56)
#define D64 "{%0,%1,%2,%3,%4,%5,%6,%7,%8,%9,%10,%11,%12,%13,%14,%15,%16,%17,%18,%19,%20,%21,%22,%23,%24,%25,%26,%27,%28,%29,%30,%31," \
            "%32,%33,%34,%35,%36,%37,%38,%39,%40,%41,%42,%43,%44,%45,%46,%47,%48,%49,%50,%51,%52,%53,%54,%55,%56,%57,%58,%59,%60,%61,%62,%63}"
template <int TB>
__device__ __forceinline__ void mma_rs(float (&d)[64], uint32_t a0, uint32_t a1, uint32_t a2, uint32_t a3, uint64_t db, int acc) {
  asm volatile("{\n.reg .pred p;\nsetp.ne.b32 p, %70, 0;\n"
               "wgmma.mma_async.sync.aligned.m64n128k16.f32.bf16.bf16 " D64 ", {%64,%65,%66,%67}, %68, p, 1, 1, %69;\n}\n"
               : R64(d) : "r"(a0), "r"(a1), "r"(a2), "r"(a3), "l"(db), "n"(TB), "r"(acc));
}
template <int TB>
__device__ __forceinline__ void mma_ss(float (&d)[64], uint64_t da, uint64_t db, int acc) {
  asm volatile("{\n.reg .pred p;\nsetp.ne.b32 p, %67, 0;\n"
               "wgmma.mma_async.sync.aligned.m64n128k16.f32.bf16.bf16 " D64 ", %64, %65, p, 1, 1, 0, %66;\n}\n"
               : R64(d) : "l"(da), "l"(db), "n"(TB), "r"(acc));
}

#define TL(cond, i)
#define TR(id)

__device__ __forceinline__ int item_tile(int c, int n, int rank) { return n ? 7 - 2 * (c & 3) - rank : 8 + 2 * (c & 3) + rank; }
__device__ __forceinline__ int p1_kind(int j1, int rd, int u) { return ((j1 < 4 ? 0x210 : rd ? 0x102 : 0x120) >> (4 * u)) & 3; }
__device__ __forceinline__ bool p1_reload(int j1, int rd, int u) { return ((j1 < 4 ? 5 : rd ? 3 : 7) >> u) & 1; }
__device__ __forceinline__ int p3_head(int i, int kh) { return 2 * i + kh; }
template <int N> using IC = std::integral_constant<int, N>;
struct Slot {
  int s; uint32_t p;
  __device__ __forceinline__ Slot take() { const Slot r = *this; if (++s == NSLOT) { s = 0; p ^= 1; } return r; }
};

template <bool SCALE>
__device__ __forceinline__ void store_tile(uint8_t* dst, const float (&a)[64], float s0, float s1) {
#pragma unroll
  for (int hh = 0; hh < 2; hh++) {
    const float s = SCALE ? (hh ? s1 : s0) : 1.f;
#pragma unroll
    for (int J = 0; J < 4; J++) {
      uint4 v;
      v.x = pack2(a[16 * J + 2 * hh + 0] * s, a[16 * J + 2 * hh + 1] * s);
      v.y = pack2(a[16 * J + 2 * hh + 4] * s, a[16 * J + 2 * hh + 5] * s);
      v.z = pack2(a[16 * J + 2 * hh + 8] * s, a[16 * J + 2 * hh + 9] * s);
      v.w = pack2(a[16 * J + 2 * hh + 12] * s, a[16 * J + 2 * hh + 13] * s);
      *reinterpret_cast<uint4*>(dst + hh * 2048 + J * 512) = v;
    }
  }
}

__device__ __forceinline__ float warp_sum(float v) {
#pragma unroll
  for (int o = 16; o; o >>= 1) v += __shfl_xor_sync(0xffffffffu, v, o);
  return v;
}

__device__ void side_work(const Params& p, uint8_t* smem, int q) {
  const int tid = threadIdx.x;
  const unsigned ep = g_epoch[blockIdx.x] + 1;
  float* s_x = reinterpret_cast<float*>(smem);
  float* s_h = s_x + 512;
  float* s_red = s_h + 384;
  unsigned long long* s_key = reinterpret_cast<unsigned long long*>(s_red + 8 * 2 * 344);
  for (int r = tid; r < DM; r += 384) {
    prefetch_l2(p.w_gate + (size_t)r * FF + q * 344, 688);
    prefetch_l2(p.w_up + (size_t)r * FF + q * 344, 688);
  }
  if (tid < 43) prefetch_l2(p.w_down + (size_t)(q * 344 + tid * 8) * DM, 8192);
  if (tid < 64) flag_wait(&g_fln[64 * q + tid], ep);
  __syncthreads();
  unsigned long long key = 0;
  {
    const int lane = tid & 31;
    const uint4 wa = __ldg(reinterpret_cast<const uint4*>(p.w_r) + lane), wb = __ldg(reinterpret_cast<const uint4*>(p.w_r) + 32 + lane);
    const uint32_t w[8] = {wa.x, wa.y, wa.z, wa.w, wb.x, wb.y, wb.z, wb.w};
#pragma unroll 4
    for (int row = 512 * q + (tid >> 5); row < 512 * q + 512; row += 12) {
      const uint4 a = __ldcg(reinterpret_cast<const uint4*>(g_xn + row * DM) + lane);
      const uint4 b = __ldcg(reinterpret_cast<const uint4*>(g_xn + row * DM) + 32 + lane);
      const uint32_t v[8] = {a.x, a.y, a.z, a.w, b.x, b.y, b.z, b.w};
      float dot = 0.f;
#pragma unroll
      for (int i = 0; i < 8; i++) dot = fmaf(bf_lo(v[i]), bf_lo(w[i]), fmaf(bf_hi(v[i]), bf_hi(w[i]), dot));
      uint32_t u = __float_as_uint(rbf(warp_sum(dot)));
      u = (u & 0x80000000u) ? ~u : (u | 0x80000000u);
      const unsigned long long k = ((unsigned long long)u << 32) | (unsigned)(SEQ - 1 - row);
      key = k > key ? k : key;
    }
  }
  if ((tid & 31) == 0) s_key[tid >> 5] = key;
  __syncthreads();
  if (tid == 0) {
    for (int w = 1; w < 12; w++) key = s_key[w] > key ? s_key[w] : key;
    g_key[q] = key;
    flag_set(&g_fy[4 + q], ep);
  }
  if (tid < 4) flag_wait(&g_fy[4 + tid], ep);
  __syncthreads();
#pragma unroll
  for (int w = 0; w < 4; w++) { const unsigned long long k = __ldcg(&g_key[w]); key = k > key ? k : key; }
  const int idx = SEQ - 1 - (int)(key & 0xffffffffu);
  for (int i = tid; i < DM; i += 384) s_x[i] = __bfloat162float(__ldcg(&g_xn[idx * DM + i]));
  __syncthreads();
  if (tid < 344) {
    const int cc = tid % 43, kg = tid / 43;
    float ag[8], au[8];
#pragma unroll
    for (int i = 0; i < 8; i++) ag[i] = au[i] = 0.f;
    const uint4* pg = reinterpret_cast<const uint4*>(p.w_gate + (size_t)(kg * 64) * FF + q * 344 + cc * 8);
    const uint4* pu = reinterpret_cast<const uint4*>(p.w_up + (size_t)(kg * 64) * FF + q * 344 + cc * 8);
#pragma unroll 8
    for (int k = 0; k < 64; k++) {
      const uint4 a = __ldg(pg + k * (FF / 8)), b = __ldg(pu + k * (FF / 8));
      const float xv = s_x[kg * 64 + k];
      ag[0] += xv * bf_lo(a.x); ag[1] += xv * bf_hi(a.x); ag[2] += xv * bf_lo(a.y); ag[3] += xv * bf_hi(a.y);
      ag[4] += xv * bf_lo(a.z); ag[5] += xv * bf_hi(a.z); ag[6] += xv * bf_lo(a.w); ag[7] += xv * bf_hi(a.w);
      au[0] += xv * bf_lo(b.x); au[1] += xv * bf_hi(b.x); au[2] += xv * bf_lo(b.y); au[3] += xv * bf_hi(b.y);
      au[4] += xv * bf_lo(b.z); au[5] += xv * bf_hi(b.z); au[6] += xv * bf_lo(b.w); au[7] += xv * bf_hi(b.w);
    }
#pragma unroll
    for (int i = 0; i < 8; i++) {
      s_red[(kg * 2 + 0) * 344 + cc * 8 + i] = ag[i];
      s_red[(kg * 2 + 1) * 344 + cc * 8 + i] = au[i];
    }
  }
  __syncthreads();
  if (tid < 344) {
    float g = 0.f, u = 0.f;
#pragma unroll
    for (int kg = 0; kg < 8; kg++) { g += s_red[(kg * 2) * 344 + tid]; u += s_red[(kg * 2 + 1) * 344 + tid]; }
    g = rbf(g); u = rbf(u);
    const float sg = rbf(g / (1.f + expf(-g)));
    s_h[tid] = rbf(sg * u);
  }
  __syncthreads();
  {
    const int cc = tid & 63, fg = tid >> 6;
    float a8[8];
#pragma unroll
    for (int i = 0; i < 8; i++) a8[i] = 0.f;
    const uint4* pd = reinterpret_cast<const uint4*>(p.w_down + (size_t)(q * 344) * DM + cc * 8);
#pragma unroll 8
    for (int f = fg; f < 344; f += 6) {
      const uint4 a = __ldg(pd + f * (DM / 8));
      const float hv = s_h[f];
      a8[0] += hv * bf_lo(a.x); a8[1] += hv * bf_hi(a.x); a8[2] += hv * bf_lo(a.y); a8[3] += hv * bf_hi(a.y);
      a8[4] += hv * bf_lo(a.z); a8[5] += hv * bf_hi(a.z); a8[6] += hv * bf_lo(a.w); a8[7] += hv * bf_hi(a.w);
    }
#pragma unroll
    for (int i = 0; i < 8; i++) s_red[fg * DM + cc * 8 + i] = a8[i];
  }
  __syncthreads();
  for (int i = tid; i < DM; i += 384) {
    float y = 0.f;
#pragma unroll
    for (int fg = 0; fg < 6; fg++) y += s_red[fg * DM + i];
    g_ypart[q * DM + i] = y;
  }
  if (tid == 0) {
    const uint32_t u = (uint32_t)(key >> 32);
    const float r = __uint_as_float((u & 0x80000000u) ? u & 0x7fffffffu : ~u);
    g_sel[q * 2] = __int_as_float(idx);
    g_sel[q * 2 + 1] = rbf(1.f / (1.f + expf(-r)));
  }
  __syncthreads();
  if (tid == 0) {
    flag_set(&g_fy[q], ep);
    g_epoch[blockIdx.x] = ep;
  }
}

__device__ __forceinline__ void ld_row(uint32_t (&v)[8], const bf16* src, int lane) {
  asm volatile("ld.global.nc.v4.u32 {%0, %1, %2, %3}, [%4];" : "=r"(v[0]), "=r"(v[1]), "=r"(v[2]), "=r"(v[3]) : "l"(src + lane * 8));
  asm volatile("ld.global.nc.v4.u32 {%0, %1, %2, %3}, [%4];" : "=r"(v[4]), "=r"(v[5]), "=r"(v[6]), "=r"(v[7]) : "l"(src + 256 + lane * 8));
}
__device__ __forceinline__ void ln_row(uint32_t (&v)[8], int row, int lane) {
  float s = 0.f;
#pragma unroll
  for (int i = 0; i < 8; i++) s += bf_lo(v[i]) + bf_hi(v[i]);
  const float mean = warp_sum(s) * (1.f / DM);
  float q = 0.f;
#pragma unroll
  for (int i = 0; i < 8; i++) {
    const float d0 = bf_lo(v[i]) - mean, d1 = bf_hi(v[i]) - mean;
    q = fmaf(d0, d0, fmaf(d1, d1, q));
  }
  const float var = rbf(warp_sum(q) * (1.f / DM));
  const float m = rbf(mean);
  float den, rc;
  asm("sqrt.approx.ftz.f32 %0, %1;" : "=f"(den) : "f"(rbf(var + 1e-5f)));
  asm("rcp.approx.ftz.f32 %0, %1;" : "=f"(rc) : "f"(rbf(den)));
#pragma unroll
  for (int i = 0; i < 8; i++) {
    const uint32_t d = pack2(bf_lo(v[i]) - m, bf_hi(v[i]) - m);
    v[i] = pack2(bf_lo(d) * rc, bf_hi(d) * rc);
  }
  uint4* dst = reinterpret_cast<uint4*>(g_xn + row * DM);
  dst[lane] = make_uint4(v[0], v[1], v[2], v[3]);
  dst[32 + lane] = make_uint4(v[4], v[5], v[6], v[7]);
}

__global__ void __cluster_dims__(2, 1, 1) __launch_bounds__(384, 1)
fused_kernel(const __grid_constant__ CUtensorMap tm_c, const __grid_constant__ CUtensorMap tm_xn,
             const __grid_constant__ CUtensorMap tm_wuk, const __grid_constant__ CUtensorMap tm_wuv,
             const __grid_constant__ CUtensorMap tm_wq, const __grid_constant__ CUtensorMap tm_wo,
             const __grid_constant__ Params p) {
  extern __shared__ uint8_t smem_raw[];
  const int c = blockIdx.x >> 1, rank = blockIdx.x & 1;
  if (c >= 64) { side_work(p, smem_raw, blockIdx.x - 128); return; }

  const uint32_t ring = (smem_u32(smem_raw) + 1023) & ~1023u;
  const uint32_t bar_full = ring + NSLOT * TILE, bar_pf = bar_full + 56, bar_empty = bar_full + 64;
  const uint32_t bar_done = bar_full + 128;
  const uint32_t bar_sel = bar_full + 120, bar_ln = bar_full + 272;
  const uint32_t sel_box = bar_full + 288;
  const uint32_t bar_dep = bar_full + 304;
  const uint32_t bar_row = bar_full + 376;
  const uint32_t upd_box = bar_full + 400;
  const int warp = __shfl_sync(0xffffffffu, threadIdx.x >> 5, 0), lane = threadIdx.x & 31;

  const int j1 = c & 7, r1 = 2 * j1 + rank, g1 = c >> 3;
  const int h2 = c >> 2;
  const int kh = c & 1, nb = (c >> 1) & 3, j3 = c >> 3, r3 = 2 * j3 + rank;
  const int sp = 9 + 2 * (c & 3);

  uint32_t lnx[2][8];
  if ((warp >> 2) == 1) {
    ld_row(lnx[0], p.x + (1024 + blockIdx.x * 8 + 2 * (warp & 3)) * DM, lane);
    ld_row(lnx[1], p.x + (1025 + blockIdx.x * 8 + 2 * (warp & 3)) * DM, lane);
  }
  TL(threadIdx.x == 0, 0);
  if (warp == 8) {
    if (lane == 0) {
#pragma unroll
      for (int i = 0; i < NSLOT; i++) mbar_init(bar_full + 8 * i, 1);
      asm volatile("fence.mbarrier_init.release.cluster;" ::: "memory");
    }
    __syncwarp();
    for (int i = 0; i < 2; i++) fill_3d(ring + i * TILE, &tm_c, bar_full + 8 * i, r1 * 128, 4 * i);
    if (lane == 0 && j1 < 4)
      asm volatile("cp.async.bulk.prefetch.tensor.2d.L2.global [%0, {%1, %2}];" ::"l"(&tm_wuk), "r"(g1 * 256 + rank * 64), "r"(j1 * 128) : "memory");
  } else if (threadIdx.x == 288) {
#pragma unroll
    for (int i = 0; i < NSLOT; i++) mbar_init(bar_empty + 8 * i, 16);
    mbar_init(bar_ln, 4); mbar_init(bar_ln + 8, 3); mbar_init(bar_pf, 1); mbar_init(bar_sel, 1);
    asm volatile("fence.mbarrier_init.release.cluster;" ::: "memory");
  } else if (threadIdx.x == 320) {
#pragma unroll
    for (int i = 0; i < 10; i++) mbar_init(bar_dep + 8 * i, 1);
    asm volatile("fence.mbarrier_init.release.cluster;" ::: "memory");
  } else if (threadIdx.x == 352) {
    prefetch_l2(p.x + blockIdx.x * 8 * DM, 8192);
#pragma unroll
    for (int i = 0; i < 9; i++) mbar_init(bar_done + 8 * i, 8);
  } else if (threadIdx.x == 0) {
#pragma unroll
    for (int i = 9; i < 18; i++) mbar_init(bar_done + 8 * i, i < 17 ? 8 : 1);
  }
  __syncthreads();
  asm volatile("barrier.cluster.arrive.relaxed.aligned;\nbarrier.cluster.wait.aligned;" ::: "memory");

  if (warp >= 8) {
    asm volatile("setmaxnreg.dec.sync.aligned.u32 40;");
    if (warp == 8) {
      int nxt = 2;
      uint32_t pm = 0x7c, dst, fb;
      auto grab = [&](int x) {
        mbar_spin(bar_empty + 8 * x, (pm >> x) & 1);
        pm ^= 1u << x;
        dst = ring + x * TILE;
        TR(x);
      };
      auto acquire = [&]() { grab(nxt); fb = bar_full + 8 * nxt; nxt = nxt == NSLOT - 1 ? 0 : nxt + 1; };
      auto dep = [&](int i) { mbar_spin(bar_dep + 8 * i, 0); };
      const uint8_t* kb = g_k + (size_t)h2 * 16 * TILE;
      const uint8_t* vb = g_v + (size_t)h2 * 16 * TILE;
#pragma unroll 1
      for (int rd = 0; rd < 2; rd++) {
#pragma unroll 1
        for (int t = 0; t < 6; t++) {
          const int kind = p1_kind(j1, rd, t >> 1);
          const bool ld = !(t & 1) && p1_reload(j1, rd, t >> 1);
          const CUtensorMap* tw = kind == 0 ? &tm_wuk : kind == 1 ? &tm_wuv : &tm_wq;
          const CUtensorMap* ta = kind < 2 ? &tm_c : &tm_xn;
          const int col = (16 * rd + 2 * g1 + (t & 1)) * 128 + rank * 64;
          int a0 = 0;
          if (kind == 2) dep(0);
          if (ld && (rd | t)) {
            a0 = nxt;
            for (int i = 0; i < 2; i++) { acquire(); fill_3d(dst, ta, fb, r1 * 128, 4 * i); }
          }
#pragma unroll 1
          for (int st = 0; st < 4; st++) {
            acquire(); fill_2d_mc(dst + rank * 16384, tw, fb, col, st * 128);
            if (ld && st == 3) { acquire(); fill_3d(dst, ta, fb, r1 * 128 + 64, 4); }
            if (ld && st == (t ? 1 : 3)) { grab(a0); fill_3d(dst, ta, bar_row, r1 * 128 + 64, 0); }
          }

        }
        auto load_q = [&](int n) { acquire(); fill_bulk(dst, g_q + (size_t)((16 * rd + h2) * 16 + item_tile(c, n, rank)) * TILE, fb); };
        auto load_kv = [&](const uint8_t* base, int s) {
          acquire();
          if (s == sp) fill_bulk(dst, base + (size_t)(rank ? sp : NSTEP - 1 - sp) * TILE, fb);
          else fill_bulk_mc(dst + rank * 16384, base + (size_t)(s < sp ? s : NSTEP - 1 - s) * TILE + rank * 16384, fb);
        };
        dep(1 + 2 * rd);
        load_q(0);
        load_kv(kb, 0);
#pragma unroll 1
        for (int n = 1; n < NSTEP; n++) {
          if (n == 8) dep(2 + 2 * rd);
          if (n == sp && rank == 0) load_q(1);
          load_kv(kb, n);
          if (n == sp && rank == 1) load_q(1);
          load_kv(vb, n - 1);
          if (n == PF_STEP) mbar_arrive_lt(bar_pf, lane, 1);
        }
        load_kv(vb, NSTEP - 1);
      }
#pragma unroll 1
      for (int i = 0; i < 16; i++) {
        const int h = p3_head(i, kh);
        if ((i & 7) == 0) dep(6 + (i >> 3));
        acquire(); fill_bulk(dst, g_q + (size_t)(h * 16 + r3) * TILE, fb);
        acquire(); fill_2d_mc(dst + rank * 16384, &tm_wo, fb, nb * 128 + ((rank ^ kh) & 1) * 64, h * 128);
      }
    } else {
      const unsigned ep = g_epoch[blockIdx.x] + 1;
      if (threadIdx.x == 288) asm volatile("st.shared.b32 [%0], %1;" ::"r"(sel_box + 4), "r"(ep) : "memory");
#pragma unroll 1
      for (int r = 2 * (warp - 9); r < (warp == 11 ? 8 : 2 * (warp - 8)); r++) {
        uint32_t v[8];
        ld_row(v, p.x + (blockIdx.x * 8 + r) * DM, lane);
        if (r == 1 && lane == 0) {
          mbar_wait(bar_ln, 0);
          flag_set(&g_fln[128 + blockIdx.x], ep);
        }
        __syncwarp();
        ln_row(v, blockIdx.x * 8 + r, lane);
      }
      __syncwarp();
      if (lane == 0) mbar_arrive(bar_ln + 8);
      TL(threadIdx.x == 352, 60);
      if (warp == 9) {
        if (lane == 0) {
          mbar_wait(bar_ln + 8, 0);
          flag_set(&g_fln[blockIdx.x], ep);
        }
#pragma unroll 1
        for (int i = 0; i < 16; i++) {
          if (lane == 0) {
            const int t = i & 7, hb = 16 * (i >> 3);
            unsigned* f;
            if (t < 6) f = &g_fp[(p1_kind(j1, i >> 3, t >> 1) * NH + hb + 2 * g1 + (t & 1)) * 16 + r1];
            else f = &g_fc[(hb + h2) * 16 + item_tile(c, t & 1, rank)];
            mbar_wait(bar_done + 8 * i, 0);
            flag_set(f, ep);
          }
          __syncwarp();
          if (i == 13) {
            if (lane < 4) flag_wait(&g_fy[lane], ep);
            __syncwarp();
            const int idx = __float_as_int(__ldcg(&g_sel[0]));
            if ((idx >> 7) == r3) {
              const float rs = __ldcg(&g_sel[1]);
              float y0 = 0.f, y1 = 0.f;
#pragma unroll
              for (int q = 0; q < 4; q++) {
                const float2 y = __ldcg(reinterpret_cast<const float2*>(g_ypart + q * DM + nb * 128 + kh * 64) + lane);
                y0 += y.x; y1 += y.y;
              }
              asm volatile("st.shared.b32 [%0], %1;" ::"r"(upd_box + 4 * lane), "r"(pack2(rbf(y0) * rs, rbf(y1) * rs)) : "memory");
            }
            if (lane == 0) asm volatile("st.shared.b32 [%0], %1;" ::"r"(sel_box), "r"(idx) : "memory");
            __syncwarp();
            if (lane == 0) mbar_arrive(bar_sel);
          }
        }
        if (lane == 0) {
          mbar_wait(bar_done + 8 * 16, 0);
          g_epoch[blockIdx.x] = ep;
        }
      } else if (warp == 10) {
        auto fwd = [&](int i) {
          __syncwarp();
          if (lane == 0) { fence_async_global(); mbar_arrive(bar_dep + 8 * i); }
        };
        if (lane < 16) flag_wait(&g_fln[16 * r1 + lane], ep);
        fwd(0);
#pragma unroll 1
        for (int rd = 0; rd < 2; rd++) {
          const int h = 16 * rd + h2;
          for (int n = 0; n < 2; n++) {
            mbar_wait(bar_done + 8 * (8 * rd + 3 + 2 * n), 0);
            if (lane < 17) flag_wait(&g_fp[((lane >> 3) * NH + h) * 16 + (lane < 16 ? 8 * n + (lane & 7) : item_tile(c, n, rank))], ep);
            fwd(1 + 2 * rd + n);
          }
          if (rd == 0) {
            mbar_wait(bar_done + 8 * 17, 0);
            if (lane < 16) flag_wait(&g_fw[16 * g1 + lane], ep);
            fwd(5);
            if (lane < 16) flag_wait(&g_fc[(2 * g1 + (lane >> 3)) * 16 + (lane & 7)], ep);
            fwd(8);
          }
        }
        if (lane < 8) flag_wait(&g_fc[p3_head(lane, kh) * 16 + r3], ep);
        fwd(6);
        mbar_wait(bar_done + 8 * 15, 0);
        if (lane < 8) flag_wait(&g_fc[p3_head(8 + lane, kh) * 16 + r3], ep);
        fwd(7);
      } else if (lane < 4) {
        const size_t off = (size_t)(blockIdx.x * 4 + lane) * 8192;
        prefetch_l2(p.wuv + off, 4096);
        prefetch_l2(p.wq + off, 4096);
        mbar_wait(bar_pf, 0);
        prefetch_l2(p.c + off / 2, 4096);
        prefetch_l2(reinterpret_cast<const uint8_t*>(g_xn) + off / 2, 4096);
        prefetch_l2(p.wuk + off + 4096, 4096);
        prefetch_l2(p.wq + off + 4096, 4096);
        mbar_wait(bar_done + 8 * 7, 0);
        prefetch_l2(p.wuv + off + 4096, 4096);
        mbar_wait(bar_pf, 1);
        prefetch_l2(p.wo + off, 8192);
        mbar_wait(bar_dep + 8 * 6, 0);
        prefetch_l2(g_q + (size_t)(p3_head(2 * nb + (lane >> 1), kh) * 16 + r3) * TILE + (lane & 1) * 16384, 16384);
      }
      __syncwarp();
    }
    asm volatile("barrier.cluster.arrive.relaxed.aligned;\nbarrier.cluster.wait.aligned;" ::: "memory");
  } else {
    asm volatile("setmaxnreg.inc.sync.aligned.u32 232;");
    const int wg = warp >> 2, wq = warp & 3;
    const int g = lane >> 2, t4 = lane & 3;
    const uint32_t ring_d = (ring & 0x3FFFF) >> 4;
    uint32_t empty_c;
    asm("mapa.shared::cluster.u32 %0, %1, %2;" : "=r"(empty_c) : "r"(bar_empty), "r"(lane & 1));
    auto release = [&](int slot) { mbar_arrive_cluster_lt(empty_c + 8 * slot, lane, 2); };
    auto wait_full = [&](Slot x) { mbar_spin(bar_full + 8 * x.s, x.p); };
    auto signal_done = [&](int i) { __syncwarp(); mbar_arrive_lt(bar_done + 8 * i, lane, 1); };
    const uint32_t st_off = (wg * 8 + wq * 2) * 2048 + g * 64 + ((t4 ^ (g >> 1)) << 4);
    if (wg == 1) {
      bar_arrive(1, 256);
      ln_row(lnx[0], 1024 + blockIdx.x * 8 + 2 * wq, lane);
      ln_row(lnx[1], 1025 + blockIdx.x * 8 + 2 * wq, lane);
      __syncwarp();
      mbar_arrive_lt(bar_ln, lane, 1);
      TR(5);
      TL(threadIdx.x == 128, 61);
    }
    Slot cur{0, 0};
    uint32_t row_par = 0;

    uint32_t a[128];
    Slot row2;
    bool row_pend;
    auto ld_rows = [&](int sl, auto K0, auto K1, bool last) {
      const uint32_t base = ring + sl * TILE + (wq * 16 + (lane & 7) + ((lane >> 3) & 1) * 8) * 128;
#pragma unroll
      for (int k = decltype(K0)::value; k < decltype(K1)::value; k++) {
        const uint32_t ch = ((2 * (k & 3) + (lane >> 4)) ^ (lane & 7)) << 4;
        ldsm4(base + ((k >> 2) & 3) * 8192 + ch, a[4 * k], a[4 * k + 1], a[4 * k + 2], a[4 * k + 3]);
      }
      if (last) {
        uint32_t dep = 0;
#pragma unroll
        for (int k = decltype(K0)::value; k < decltype(K1)::value; k++) dep |= a[4 * k];
        mbar_arrive_cluster_lt(empty_c + 8 * sl + (dep & p.zero), lane, 4);
      }
    };
    auto load_rows = [&]() {
      const Slot x = cur.take();
      row2 = cur.take();
      if (wg) row2 = x.s ? Slot{x.s - 1, x.p ^ 1} : Slot{NSLOT - 1, x.p};
      mbar_spin(wg ? bar_row : bar_full + 8 * x.s, wg ? row_par : x.p);
      row_par ^= 1;
      TR(40);
      ld_rows(x.s, IC<0>(), IC<16>(), true);
      row_pend = true;
      TR(42);
    };
#pragma unroll
    for (int i = 64; i < 128; i++) asm volatile("mov.b32 %0, 0;" : "=r"(a[i]));
    load_rows();
    TL(threadIdx.x == 0, 1);

#pragma unroll 1
    for (int rd = 0;; rd++) {
      uint32_t q[32];
      auto load_q = [&](Slot x) {
        const uint32_t qoff = (wg * 8 + wq * 2 + ((lane >> 3) & 1)) * 2048 + (lane & 7) * 64 + (((lane >> 4) ^ ((lane >> 1) & 3)) << 4);
        wait_full(x);
        const uint32_t base = ring + x.s * TILE + qoff;
#pragma unroll
        for (int k = 0; k < 8; k++) ldsm4((base + (k >> 1) * 512) ^ ((k & 1) * 32), q[4 * k], q[4 * k + 1], q[4 * k + 2], q[4 * k + 3]);
        uint32_t dep = 0;
#pragma unroll
        for (int k = 0; k < 8; k++) dep |= q[4 * k];
        mbar_arrive_cluster_lt(empty_c + 8 * x.s + (dep & p.zero), lane, 2);
      };
      {
        float acc[64];
        auto store_p1 = [&](int t) {
          const int kind = p1_kind(j1, rd, t >> 1), tile = (2 * g1 + (t & 1)) * 16 + r1;
          if (kind < 2) {
            if (rd) mbar_spin(bar_dep + 8 * (kind ? 8 : 5), 0);
            store_tile<false>((kind ? g_v : g_k) + (size_t)tile * TILE + st_off, acc, 1.f, 1.f);
          } else {
            const float sc = 0.08838834764831845f * 1.4426950408889634f;
            store_tile<true>(g_q + (size_t)(256 * rd + tile) * TILE + st_off, acc, sc, sc);
          }
          signal_done(8 * rd + t);
          TR(30);
          TL(threadIdx.x == 0, 2 + t + 24 * rd);
        };
#pragma unroll 1
        for (int t = 0;; t++) {
          int prev = 0;
#pragma unroll
          for (int st = 0; st < 4; st++) {
            const Slot x = cur.take();
            wait_full(x);
            TR(10 + st);
            if (st == 0) bar_sync(1 + wg, 256);
            const uint32_t lo = (ring_d + x.s * (TILE >> 4)) | DW_LO;
            wg_fence();
#pragma unroll
            for (int k = 0; k < 8; k++) {
              const int o = (st * 8 + k) * 4;
              mma_rs<1>(acc, a[o], a[o + 1], a[o + 2], a[o + 3], desc(lo + k * DW_STEP, DW_HI), st | k);
            }
            wg_commit();
            if (st == 0) TR(15);
            if (st == 0 && row_pend) {
              wait_full(row2);
              ld_rows(row2.s, IC<16>(), IC<24>(), false);
            }
            if (st == 2 && row_pend) {
              ld_rows(row2.s, IC<24>(), IC<32>(), true);
            }
            if (st == 3) bar_arrive(2 - wg, 256);
            if (st > 0) { wg_wait<1>(); release(prev); }
            prev = x.s;
          }
          if (row_pend) cur.take();
          row_pend = false;
          wg_wait<0>();
          release(prev);
          pin(acc);
          TR(20);
          if (t == 5) break;
          if ((t & 1) && p1_reload(j1, rd, (t + 1) >> 1)) load_rows();
          store_p1(t);
        }
        load_q(cur.take());
        store_p1(5);
      }

      {
        uint32_t pr[32];
        float s[64], o[64];
        float m0 = 0.f, m1 = 0.f, l0 = 0.f, l1 = 0.f, t0, t1, u0, u1;
        bool gen;
        const int mthr = wg * 64 + wq * 16 + g - 2 * t4;
        const int f1 = sp + rank;

        auto issue_qk = [&](int sl) {
          const uint32_t lo = (ring_d + sl * (TILE >> 4)) | DK_LO;
#pragma unroll
          for (int k = 0; k < 8; k++) mma_rs<0>(s, q[4 * k], q[4 * k + 1], q[4 * k + 2], q[4 * k + 3], desc(lo + dk_step(k), DK_HI), k);
        };
        auto issue_pv = [&](int sl, int keep) {
          const uint32_t lo = (ring_d + sl * (TILE >> 4)) | DN_LO;
#pragma unroll
          for (int k = 0; k < 8; k++) {
            mma_rs<1>(o, pr[4 * k], pr[4 * k + 1], pr[4 * k + 2], pr[4 * k + 3], desc(lo + k * DN_STEP, DN_HI), k ? 1 : keep);
            if (k == PV_A - 1 || k == PV_B - 1 || k == 7) wg_commit();
          }
        };
        auto mask = [&]() {
#pragma unroll
          for (int j = 0; j < 16; j++) {
            if (8 * j > mthr) s[4 * j] = -INFINITY;
            if (8 * j + 1 > mthr) s[4 * j + 1] = -INFINITY;
            if (8 * j - 8 > mthr) s[4 * j + 2] = -INFINITY;
            if (8 * j - 7 > mthr) s[4 * j + 3] = -INFINITY;
          }
        };
        auto fast = [&](auto J0, auto J1) {
#pragma unroll
          for (int j = decltype(J0)::value; j < decltype(J1)::value; j++) {
            const float e0 = ex2(s[4 * j]), e1 = ex2(s[4 * j + 1]), e2 = ex2(s[4 * j + 2]), e3 = ex2(s[4 * j + 3]);
            if (j == 0) { t0 = e0; u0 = e1; t1 = e2; u1 = e3; } else { t0 += e0; u0 += e1; t1 += e2; u1 += e3; }
            pr[2 * j] = pack2(e0, e1); pr[2 * j + 1] = pack2(e2, e3);
          }
#pragma unroll
          for (int j = decltype(J0)::value; j < decltype(J1)::value; j++) asm volatile("" : "+r"(pr[2 * j]), "+r"(pr[2 * j + 1]));
          asm volatile("" : "+f"(t0), "+f"(t1), "+f"(u0), "+f"(u1));
        };
        auto quad_sum = [&](float v) {
          v += __shfl_xor_sync(0xffffffffu, v, 1);
          return v + __shfl_xor_sync(0xffffffffu, v, 2);
        };
        auto too_big = [&]() {
          t0 += u0; t1 += u1;
          return (bool)__any_sync(0xffffffffu, !(t0 + t1 <= 1.125899906842624e15f));
        };
        auto too_small = [&]() { return (bool)__any_sync(0xffffffffu, !(fminf(quad_sum(t0), quad_sum(t1)) >= 9.313225746154785e-10f)); };
        auto online = [&](bool first) {
          float x0 = fmaxf(s[0], s[1]), x1 = fmaxf(s[2], s[3]);
#pragma unroll
          for (int j = 1; j < 16; j++) {
            x0 = fmaxf(x0, fmaxf(s[4 * j], s[4 * j + 1])); x1 = fmaxf(x1, fmaxf(s[4 * j + 2], s[4 * j + 3]));
          }
          x0 = fmaxf(x0, __shfl_xor_sync(0xffffffffu, x0, 1)); x1 = fmaxf(x1, __shfl_xor_sync(0xffffffffu, x1, 1));
          x0 = fmaxf(x0, __shfl_xor_sync(0xffffffffu, x0, 2)); x1 = fmaxf(x1, __shfl_xor_sync(0xffffffffu, x1, 2));
          if (!first) {
            x0 = fmaxf(x0, m0); x1 = fmaxf(x1, m1);
            const float a0 = ex2(m0 - x0), a1 = ex2(m1 - x1);
            l0 *= a0; l1 *= a1;
#pragma unroll
            for (int j = 0; j < 16; j++) { o[4 * j] *= a0; o[4 * j + 1] *= a0; o[4 * j + 2] *= a1; o[4 * j + 3] *= a1; }
          }
          m0 = x0; m1 = x1;
          t0 = t1 = 0.f;
#pragma unroll
          for (int j = 0; j < 16; j++) {
            const float e0 = ex2(s[4 * j] - x0), e1 = ex2(s[4 * j + 1] - x0), e2 = ex2(s[4 * j + 2] - x1), e3 = ex2(s[4 * j + 3] - x1);
            t0 += e0 + e1; t1 += e2 + e3;
            pr[2 * j] = pack2(e0, e1); pr[2 * j + 1] = pack2(e2, e3);
          }
        };
        auto finish_item = [&](int n) {
          const float r0 = __fdividef(1.f, quad_sum(l0)), r1_ = __fdividef(1.f, quad_sum(l1));
          store_tile<true>(g_q + (size_t)((16 * rd + h2) * 16 + item_tile(c, n, rank)) * TILE + st_off, o, r0, r1_);
          signal_done(8 * rd + 6 + n);
          TR(53);
        };
        using I0 = IC<0>; using IA = IC<2 * PV_A>; using IB = IC<2 * PV_B>; using I16 = IC<16>;

        Slot ck = cur.take(), cq = ck, cv;
        auto plan = [&](int n) {
          if (n == sp && rank == 0) cq = cur.take();
          ck = cur.take();
          if (n == sp && rank == 1) cq = cur.take();
          cv = ck;
          if (n < NSTEP) cv = cur.take();
        };
        wait_full(ck);
        bar_sync(1 + wg, 256);
        wg_fence();
        issue_qk(ck.s);
        wg_commit();
        bar_arrive(2 - wg, 256);
        {
          const int sk = ck.s;
          plan(1);
          wait_full(ck);
          wait_full(cv);
          wg_wait<0>();
          pin(s);
          release(sk);
        }
        fast(I0(), I16());
        gen = too_big();
        gen |= too_small();
        if (__builtin_expect(gen, 0)) online(true);
        l0 = t0; l1 = t1;
#pragma unroll
        for (int i = 0; i < 64; i++) o[i] = 0.f;
        TR(50);
        TL(threadIdx.x == 0, 8 + 24 * rd);
        int keep = 0;
#pragma unroll 1
        for (int n = 1; n < NSTEP; n++) {
          const int sk = ck.s, sv = cv.s;
          bar_sync(1 + wg, 256);
          wg_fence();
          issue_qk(sk);
          issue_pv(sv, keep);
          bar_arrive(2 - wg, 256);
          if (n == NSTEP - 1 && rd == 0 && warp == 0)
            asm volatile("{\n.reg .pred p;\n.reg .b32 e;\nelect.sync _|p, 0xffffffff;\nld.shared.b32 e, [%1];\n"
                         "@p st.relaxed.gpu.global.u32 [%0], e;\n@p mbarrier.arrive.shared::cta.b64 _, [%2];\n}\n"
                         ::"l"(&g_fw[blockIdx.x]), "r"(sel_box + 4), "r"(bar_done + 8 * 17) : "memory");
          plan(n + 1);
          const bool okk = mbar_test(bar_full + 8 * ck.s, ck.p), okv = mbar_test(bar_full + 8 * cv.s, cv.p);
          const bool first = n == f1, edge = (unsigned)(f1 - n) < 2u;
          keep = !first;
          gen &= !first;
          wg_wait<2>();
          pin(s);
          release(sk);
          if (edge) mask();
          if (!gen) fast(I0(), IA());
          wg_wait<1>();
          if (!gen) fast(IA(), IB());
          wg_wait<0>();
          pin(o);
          release(sv);
          if (!gen) {
            fast(IB(), I16());
            gen = too_big();
          }
          if (edge | gen | !okk | !okv) {
            if (first) {
              gen |= too_small();
              finish_item(0);
              l0 = l1 = m0 = m1 = 0.f;
            }
            if (gen) online(first);
            if (n + 1 == f1) load_q(cq);
            wait_full(ck);
            wait_full(cv);
          }
          l0 += t0; l1 += t1;
          TL(threadIdx.x == 0 && (TL_STEPS || n == 1 || n == NSTEP - 1), 8 + n + 24 * rd);
        }
        TR(51);
        bar_sync(1 + wg, 256);
        wg_fence();
        issue_pv(cv.s, keep);
        if (wg == 0 || rd == 0) bar_arrive(2 - wg, 256);
        wg_wait<0>();
        pin(o);
        release(cv.s);
        TR(52);
        if (rd) { finish_item(1); break; }
        load_rows();
        finish_item(1);
#pragma unroll
        for (int i = 64; i < 128; i++) asm volatile("mov.b32 %0, 0;" : "=r"(a[i]));
      }
    }
    TL(threadIdx.x == 0, 49);

    {
      float acc[64];
#pragma unroll
      for (int i = 0; i < 64; i++) acc[i] = 0.f;
#pragma unroll 1
      for (int i = 0;; i++) {
        const Slot xa = cur.take(), xb = cur.take();
        wait_full(xa);
        TR(60);
        wait_full(xb);
        TR(61);
        const uint32_t alo = (ring_d + xa.s * (TILE >> 4) + wg * 1024) | DK_LO, blo = (ring_d + xb.s * (TILE >> 4)) | DW_LO;
        wg_fence();
#pragma unroll
        for (int k = 0; k < 8; k++) mma_ss<1>(acc, desc(alo + dk_step(k), DK_HI), desc(blo + k * DW_STEP, DW_HI), 1);
        wg_commit();
        if (i == 15) break;
        wg_wait<0>();
        release(xa.s);
        release(xb.s);
      }
      const int row = r3 * 128 + wg * 64 + wq * 16 + g, col = nb * 128 + kh * 64 + t4 * 8;
      uint4 xv[4], nv[4];
#pragma unroll
      for (int i = 0; i < 4; i++) {
        const int off = (row + (i >> 1) * 8) * DM + col + (i & 1) * 32;
        xv[i] = __ldg(reinterpret_cast<const uint4*>(p.x + off));
        nv[i] = __ldcg(reinterpret_cast<const uint4*>(g_xn + off));
      }
      mbar_spin(bar_sel, 0);
      uint32_t idx, tag;
      asm volatile("ld.shared.v2.b32 {%0, %1}, [%2];" : "=r"(idx), "=r"(tag) : "r"(sel_box) : "memory");
      tag &= 1;
      wg_wait<0>();
      pin(acc);
      TR(62);
      TL(threadIdx.x == 0, 50);
      uint4* mine = g_part + (blockIdx.x * 8 + warp) * 256 + lane;
#pragma unroll
      for (int i = 0; i < 8; i++) {
        uint32_t w[4];
#pragma unroll
        for (int e = 0; e < 4; e++) w[e] = (__float_as_uint(acc[32 + 4 * i + e]) & ~1u) | tag;
        asm volatile("st.volatile.global.v4.u32 [%0], {%1, %2, %3, %4};" ::"l"(mine + i * 32), "r"(w[0]), "r"(w[1]), "r"(w[2]), "r"(w[3]) : "memory");
      }
      const uint4* theirs = g_part + ((blockIdx.x ^ 2) * 8 + warp) * 256 + lane;
      uint32_t y[32], miss;
      if (lane == 31) {
        while (true) {
          asm volatile("ld.volatile.global.u32 %0, [%1];" : "=r"(miss) : "l"(theirs + 7 * 32) : "memory");
          if (!((miss ^ tag) & 1)) break;
          __nanosleep(64);
        }
      }
      __syncwarp();
      do {
#pragma unroll
        for (int i = 0; i < 8; i++)
          asm volatile("ld.volatile.global.v4.u32 {%0, %1, %2, %3}, [%4];"
                       : "=r"(y[4 * i]), "=r"(y[4 * i + 1]), "=r"(y[4 * i + 2]), "=r"(y[4 * i + 3]) : "l"(theirs + i * 32) : "memory");
        miss = 0;
#pragma unroll
        for (int i = 0; i < 32; i++) miss |= y[i] ^ tag;
      } while (__any_sync(0xffffffffu, miss & 1));
      uint32_t u[16];
#pragma unroll
      for (int i = 0; i < 8; i++) {
        u[i] = pack2(acc[4 * i] + __uint_as_float(y[4 * i]), acc[4 * i + 1] + __uint_as_float(y[4 * i + 1]));
        u[8 + i] = pack2(acc[4 * i + 2] + __uint_as_float(y[4 * i + 2]), acc[4 * i + 3] + __uint_as_float(y[4 * i + 3]));
      }
      TR(63);
      TL(threadIdx.x == 0, 51);
#pragma unroll
      for (int i = 0; i < 4; i++) {
        uint32_t a0 = u[4 * i], a1 = u[4 * i + 1], a2 = u[4 * i + 2], a3 = u[4 * i + 3];
        {
          const bool od = t4 & 1;
          const uint32_t e0 = __shfl_xor_sync(0xffffffffu, od ? a0 : a1, 1), e1 = __shfl_xor_sync(0xffffffffu, od ? a2 : a3, 1);
          if (od) { a0 = e0; a2 = e1; } else { a1 = e0; a3 = e1; }
          const bool hi = t4 & 2;
          const uint32_t f0 = __shfl_xor_sync(0xffffffffu, hi ? a0 : a2, 2), f1 = __shfl_xor_sync(0xffffffffu, hi ? a1 : a3, 2);
          if (hi) { a0 = f0; a1 = f1; } else { a2 = f0; a3 = f1; }
        }
        const uint32_t av[4] = {a0, a1, a2, a3};
        const uint32_t xx[4] = {xv[i].x, xv[i].y, xv[i].z, xv[i].w};
        uint32_t nn[4] = {nv[i].x, nv[i].y, nv[i].z, nv[i].w};
        const int rr = row + (i >> 1) * 8, cc = col + (i & 1) * 32;
        if (rr == (int)idx) {
          uint32_t d[4];
          asm volatile("ld.shared.v4.b32 {%0, %1, %2, %3}, [%4];" : "=r"(d[0]), "=r"(d[1]), "=r"(d[2]), "=r"(d[3])
                       : "r"(upd_box + (i & 1) * 64 + t4 * 16) : "memory");
#pragma unroll
          for (int e = 0; e < 4; e++) nn[e] = pack2(bf_lo(nn[e]) + bf_lo(d[e]), bf_hi(nn[e]) + bf_hi(d[e]));
        }
        uint32_t ov[4];
#pragma unroll
        for (int e = 0; e < 4; e++) {
          const uint32_t z = pack2(bf_lo(xx[e]) + bf_lo(av[e]), bf_hi(xx[e]) + bf_hi(av[e]));
          ov[e] = pack2(bf_lo(z) + bf_lo(nn[e]), bf_hi(z) + bf_hi(nn[e]));
        }
        *reinterpret_cast<uint4*>(p.out + rr * DM + cc) = make_uint4(ov[0], ov[1], ov[2], ov[3]);
      }
      signal_done(16);
      TR(64);
      TL(threadIdx.x == 0, 53);
    }
    asm volatile("barrier.cluster.arrive.relaxed.aligned;" ::: "memory");
  }
}

typedef CUresult (*EncodeFn)(CUtensorMap*, CUtensorMapDataType, cuuint32_t, void*, const cuuint64_t*, const cuuint64_t*,
                             const cuuint32_t*, const cuuint32_t*, CUtensorMapInterleave, CUtensorMapSwizzle,
                             CUtensorMapL2promotion, CUtensorMapFloatOOBfill);

static void make_act_map(EncodeFn enc, CUtensorMap* m, void* ptr) {
  cuuint64_t gd[3] = {64, SEQ, 8}, gs[2] = {DM * 2, 128};
  cuuint32_t bd[3] = {64, 64, 4}, es[3] = {1, 1, 1};
  enc(m, CU_TENSOR_MAP_DATA_TYPE_BFLOAT16, 3, ptr, gd, gs, bd, es, CU_TENSOR_MAP_INTERLEAVE_NONE, CU_TENSOR_MAP_SWIZZLE_128B,
      CU_TENSOR_MAP_L2_PROMOTION_L2_256B, CU_TENSOR_MAP_FLOAT_OOB_FILL_NONE);
}
static void make_w_map(EncodeFn enc, CUtensorMap* m, void* ptr, int rows, int cols) {
  cuuint64_t gd[2] = {(cuuint64_t)cols, (cuuint64_t)rows}, gs[1] = {(cuuint64_t)cols * 2};
  cuuint32_t bd[2] = {64, 128}, es[2] = {1, 1};
  enc(m, CU_TENSOR_MAP_DATA_TYPE_BFLOAT16, 2, ptr, gd, gs, bd, es, CU_TENSOR_MAP_INTERLEAVE_NONE, CU_TENSOR_MAP_SWIZZLE_128B,
      CU_TENSOR_MAP_L2_PROMOTION_L2_256B, CU_TENSOR_MAP_FLOAT_OOB_FILL_NONE);
}

extern "C" void kernel_launch(void* const* d_in, const int* in_sizes, int n_in, void* d_out, int out_size) {
  (void)in_sizes; (void)n_in; (void)out_size;
  void* fn = nullptr;
  cudaDriverEntryPointQueryResult qr;
  cudaGetDriverEntryPoint("cuTensorMapEncodeTiled", &fn, cudaEnableDefault, &qr);
  EncodeFn enc = (EncodeFn)fn;
  void* xn = nullptr;
  cudaGetSymbolAddress(&xn, g_xn);
  CUtensorMap tm_c, tm_xn, tm_wuk, tm_wuv, tm_wq, tm_wo;
  make_act_map(enc, &tm_c, d_in[1]);
  make_act_map(enc, &tm_xn, xn);
  make_w_map(enc, &tm_wq, d_in[2], DM, NH * 128);
  make_w_map(enc, &tm_wuk, d_in[3], DM, NH * 128);
  make_w_map(enc, &tm_wuv, d_in[4], DM, NH * 128);
  make_w_map(enc, &tm_wo, d_in[5], NH * 128, DM);
  Params p;
  p.x = (const bf16*)d_in[0];
  p.w_r = (const bf16*)d_in[7];
  p.w_gate = (const bf16*)d_in[8];
  p.w_up = (const bf16*)d_in[9];
  p.w_down = (const bf16*)d_in[10];
  p.c = (const uint8_t*)d_in[1];
  p.wq = (const uint8_t*)d_in[2];
  p.wuk = (const uint8_t*)d_in[3];
  p.wuv = (const uint8_t*)d_in[4];
  p.wo = (const uint8_t*)d_in[5];
  p.out = (bf16*)d_out;
  p.zero = 0;
  cudaFuncSetAttribute(fused_kernel, cudaFuncAttributeMaxDynamicSharedMemorySize, SMEM_BYTES);
  fused_kernel<<<132, 384, SMEM_BYTES>>>(tm_c, tm_xn, tm_wuk, tm_wuv, tm_wq, tm_wo, p);
}
```

```cpp
#include <cuda_runtime.h>
#include <cuda_bf16.h>
#include <cuda.h>
#include <stdint.h>
#include <type_traits>

typedef __nv_bfloat16 bf16;

constexpr int SEQ = 2048, DM = 512, NH = 32, FF = 1376;
constexpr int TILE = 32768;
constexpr int NSLOT = 7;
constexpr int SMEM_BYTES = NSLOT * TILE + 1024 + 1280;
constexpr int NSTEP = 17;

__device__ __align__(1024) uint8_t g_ctx[NH * 16 * TILE];
__device__ __align__(1024) uint8_t g_k[16 * 16 * TILE];
__device__ __align__(1024) uint8_t g_v[16 * 16 * TILE];
__device__ __align__(1024) bf16 g_xn[SEQ * DM];
__device__ unsigned long long g_key[4];
__device__ uint4 g_part[128 * 8 * 8 * 32];
__device__ float g_ypart[4 * DM];
__device__ float g_sel[4 * 2];
constexpr int F_KV = 0, F_CTX = 1024, F_LN = 1536, F_KR = 1664, F_KEY = 1792, F_FFN = 1796;
__device__ unsigned g_flag[1800];
__device__ unsigned g_epoch[132];

struct Params {
  const bf16* x;
  bf16* xn;
  uint32_t zero;
  bf16* out;
  const bf16 *w_r, *w_down;
  const uint8_t *c, *wo;
};

__device__ __forceinline__ uint32_t smem_u32(const void* p) { return (uint32_t)__cvta_generic_to_shared(p); }
__device__ __forceinline__ void mbar_init(uint32_t bar, uint32_t cnt) {
  asm volatile("mbarrier.init.shared::cta.b64 [%0], %1;" ::"r"(bar), "r"(cnt) : "memory");
}
__device__ __forceinline__ void mbar_arrive(uint32_t bar) {
  asm volatile("mbarrier.arrive.shared::cta.b64 _, [%0];" ::"r"(bar) : "memory");
}
__device__ __forceinline__ void mbar_arrive_lt(uint32_t bar, uint32_t i, uint32_t n) {
  asm volatile("{\n.reg .pred p;\nsetp.lt.u32 p, %1, %2;\n@p mbarrier.arrive.shared::cta.b64 _, [%0];\n}\n" ::"r"(bar), "r"(i), "r"(n) : "memory");
}
__device__ __forceinline__ void mbar_arrive_cluster_lt(uint32_t addr, uint32_t i, uint32_t n) {
  asm volatile("{\n.reg .pred p;\nsetp.lt.u32 p, %1, %2;\n@p mbarrier.arrive.shared::cluster.b64 _, [%0];\n}\n" ::"r"(addr), "r"(i), "r"(n) : "memory");
}
__device__ __forceinline__ bool mbar_try(uint32_t bar, uint32_t parity) {
  uint32_t ok;
  asm volatile("{\n.reg .pred p;\nmbarrier.try_wait.parity.shared::cta.b64 p, [%1], %2, %3;\nselp.u32 %0, 1, 0, p;\n}\n"
               : "=r"(ok) : "r"(bar), "r"(parity), "r"(1000000) : "memory");
  return ok;
}
__device__ __forceinline__ bool mbar_test(uint32_t bar, uint32_t parity) {
  uint32_t ok;
  asm volatile("{\n.reg .pred p;\nmbarrier.test_wait.parity.shared::cta.b64 p, [%1], %2;\nselp.u32 %0, 1, 0, p;\n}\n"
               : "=r"(ok) : "r"(bar), "r"(parity) : "memory");
  return ok;
}
__device__ __forceinline__ uint32_t ns32() { uint32_t c; asm volatile("mov.u32 %0, %%globaltimer_lo;" : "=r"(c)); return c; }
__device__ __forceinline__ void mbar_wait(uint32_t bar, uint32_t parity) {
  const uint32_t t0 = ns32();
#pragma unroll 1
  while (!mbar_try(bar, parity))
    if (ns32() - t0 > 2000000000u) __trap();
}
__device__ __forceinline__ void mbar_sleep(uint32_t bar, uint32_t parity) {
  asm volatile("{\n.reg .pred p;\nW: mbarrier.try_wait.parity.shared::cta.b64 p, [%0], %1, 1000000;\n@!p bra W;\n}\n"
               ::"r"(bar), "r"(parity) : "memory");
}
__device__ __forceinline__ void mbar_spin(uint32_t bar, uint32_t parity) {
  asm volatile("{\n.reg .pred p;\nW: mbarrier.try_wait.parity.shared::cta.b64 p, [%0], %1;\n@!p bra W;\n}\n"
               ::"r"(bar), "r"(parity) : "memory");
}
__device__ __forceinline__ unsigned ld_acquire(const unsigned* p) {
  unsigned v;
  asm volatile("ld.acquire.gpu.global.u32 %0, [%1];" : "=r"(v) : "l"(p) : "memory");
  return v;
}
__device__ __forceinline__ void flag_wait(const unsigned* p, unsigned ep, unsigned ns = 40) {
#pragma unroll 1
  while (ld_acquire(p) != ep) __nanosleep(ns);
}
__device__ __forceinline__ void flag_set(unsigned* p, unsigned ep) {
  asm volatile("fence.acq_rel.gpu;" ::: "memory");
  asm volatile("fence.proxy.async.global;" ::: "memory");
  asm volatile("st.relaxed.gpu.global.u32 [%0], %1;" ::"l"(p), "r"(ep) : "memory");
}
__device__ __forceinline__ void fence_async_global() { asm volatile("fence.proxy.async.global;" ::: "memory"); }
#define FILL_HEAD_N(n) "{\n.reg .pred p;\nelect.sync _|p, 0xffffffff;\n@p mbarrier.arrive.expect_tx.shared::cta.b64 _, [%2], " n ";\n@p "
#define FILL_HEAD FILL_HEAD_N("32768")
__device__ __forceinline__ void fill_bulk(uint32_t dst, const void* src, uint32_t bar) {
  asm volatile(FILL_HEAD "cp.async.bulk.shared::cluster.global.mbarrier::complete_tx::bytes [%0], [%1], 32768, [%2];\n}\n"
               ::"r"(dst), "l"(src), "r"(bar) : "memory");
}
__device__ __forceinline__ void fill_halves(uint32_t dst, const void* src0, const void* src1, uint32_t bar, bool use0, bool use1) {
  asm volatile("{\n.reg .pred p, q, r;\nelect.sync _|p, 0xffffffff;\nsetp.ne.and.b32 q, %5, 0, p;\nsetp.ne.and.b32 r, %6, 0, p;\n"
               "@p mbarrier.arrive.expect_tx.shared::cta.b64 _, [%3], %4;\n"
               "@r cp.async.bulk.shared::cluster.global.mbarrier::complete_tx::bytes [%0 + 16384], [%2], 16384, [%3];\n"
               "@q cp.async.bulk.shared::cluster.global.mbarrier::complete_tx::bytes [%0], [%1], 16384, [%3];\n}\n"
               ::"r"(dst), "l"(src0), "l"(src1), "r"(bar), "r"((use0 + use1) * 16384), "r"((int)use0), "r"((int)use1) : "memory");
}
__device__ __forceinline__ void fill_bulk_mc(uint32_t dst, const void* src, uint32_t bar) {
  asm volatile(FILL_HEAD "cp.async.bulk.shared::cluster.global.mbarrier::complete_tx::bytes.multicast::cluster [%0], [%1], 16384, [%2], %3;\n}\n"
               ::"r"(dst), "l"(src), "r"(bar), "h"((uint16_t)3) : "memory");
}
__device__ __forceinline__ void fill_2d_mc(uint32_t dst, const CUtensorMap* tm, uint32_t bar, int c0, int c1) {
  asm volatile(FILL_HEAD "cp.async.bulk.tensor.2d.shared::cluster.global.mbarrier::complete_tx::bytes.multicast::cluster [%0], [%1, {%3, %4}], [%2], %5;\n}\n"
               ::"r"(dst), "l"(tm), "r"(bar), "r"(c0), "r"(c1), "h"((uint16_t)3) : "memory");
}
__device__ __forceinline__ void fill_2x2d(uint32_t dst, const CUtensorMap* tm0, const CUtensorMap* tm1, uint32_t bar, int c0, int c0b, int c1) {
  asm volatile(FILL_HEAD "cp.async.bulk.tensor.2d.shared::cluster.global.mbarrier::complete_tx::bytes [%0], [%1, {%3, %4}], [%2];\n"
               "@p cp.async.bulk.tensor.2d.shared::cluster.global.mbarrier::complete_tx::bytes [%0 + 16384], [%5, {%6, %4}], [%2];\n}\n"
               ::"r"(dst), "l"(tm0), "r"(bar), "r"(c0), "r"(c1), "l"(tm1), "r"(c0b) : "memory");
}
__device__ __forceinline__ uint64_t stream_policy() { uint64_t p; asm("createpolicy.fractional.L2::evict_first.b64 %0, 1.0;" : "=l"(p)); return p; }
__device__ __forceinline__ void fill_ffn(uint32_t dst, const CUtensorMap* tm0, const CUtensorMap* tm1, uint32_t bar, int c0, int c1) {
  asm volatile(FILL_HEAD_N("22016") "cp.async.bulk.tensor.2d.shared::cluster.global.mbarrier::complete_tx::bytes.L2::cache_hint [%0], [%1, {%3, %4}], [%2], %6;\n"
               "@p cp.async.bulk.tensor.2d.shared::cluster.global.mbarrier::complete_tx::bytes.L2::cache_hint [%0 + 16384], [%5, {%3, %4}], [%2], %6;\n}\n"
               ::"r"(dst), "l"(tm0), "r"(bar), "r"(c0), "r"(c1), "l"(tm1), "l"(stream_policy()) : "memory");
}
__device__ __forceinline__ void fill_stream(uint32_t dst, const void* src, uint32_t bar, uint32_t bytes) {
  asm volatile(FILL_HEAD_N("%3") "cp.async.bulk.shared::cluster.global.mbarrier::complete_tx::bytes.L2::cache_hint [%0], [%1], %3, [%2], %4;\n}\n"
               ::"r"(dst), "l"(src), "r"(bar), "r"(bytes), "l"(stream_policy()) : "memory");
}
__device__ __forceinline__ void fill_3d(uint32_t dst, const CUtensorMap* tm, uint32_t bar, int c1, int c2) {
  asm volatile(FILL_HEAD "cp.async.bulk.tensor.3d.shared::cluster.global.mbarrier::complete_tx::bytes [%0], [%1, {%5, %3, %4}], [%2];\n}\n"
               ::"r"(dst), "l"(tm), "r"(bar), "r"(c1), "r"(c2), "r"(0) : "memory");
}
__device__ __forceinline__ void prefetch_l2(const void* p, uint32_t bytes) {
  asm volatile("{\n.reg .pred p;\nelect.sync _|p, 0xffffffff;\n@p cp.async.bulk.prefetch.L2.global [%0], %1;\n}\n" ::"l"(p), "r"(bytes) : "memory");
}
__device__ __forceinline__ void wg_fence() { asm volatile("wgmma.fence.sync.aligned;" ::: "memory"); }
__device__ __forceinline__ void wg_commit() { asm volatile("wgmma.commit_group.sync.aligned;" ::: "memory"); }
template <int N> __device__ __forceinline__ void wg_wait() { asm volatile("wgmma.wait_group.sync.aligned %0;" ::"n"(N) : "memory"); }
__device__ __forceinline__ void bar_sync(int id, int n) { asm volatile("bar.sync %0, %1;" ::"r"(id), "r"(n) : "memory"); }
__device__ __forceinline__ void bar_arrive(int id, int n) { asm volatile("bar.arrive %0, %1;" ::"r"(id), "r"(n) : "memory"); }
__device__ __forceinline__ void ldsm4(uint32_t addr, uint32_t& r0, uint32_t& r1, uint32_t& r2, uint32_t& r3) {
  asm volatile("ldmatrix.sync.aligned.m8n8.x4.shared.b16 {%0,%1,%2,%3}, [%4];"
               : "=r"(r0), "=r"(r1), "=r"(r2), "=r"(r3) : "r"(addr) : "memory");
}
__device__ __forceinline__ uint32_t pack2(float lo, float hi) {
  uint32_t r;
  asm("cvt.rn.bf16x2.f32 %0, %1, %2;" : "=r"(r) : "f"(hi), "f"(lo));
  return r;
}
__device__ __forceinline__ uint32_t add2(uint32_t a, uint32_t b) { uint32_t r; asm("add.rn.bf16x2 %0, %1, %2;" : "=r"(r) : "r"(a), "r"(b)); return r; }
__device__ __forceinline__ float ex2(float x) { float y; asm("ex2.approx.ftz.f32 %0, %1;" : "=f"(y) : "f"(x)); return y; }
__device__ __forceinline__ float bf_lo(uint32_t v) { return __uint_as_float(v << 16); }
__device__ __forceinline__ float bf_hi(uint32_t v) { return __uint_as_float(v & 0xffff0000u); }
__device__ __forceinline__ float rbf(float x) { return __bfloat162float(__float2bfloat16_rn(x)); }
template <int N> __device__ __forceinline__ void pin(float (&d)[N]) {
#pragma unroll
  for (int i = 0; i < N; i++) asm volatile("" : "+f"(d[i])::"memory");
}
template <int N> __device__ __forceinline__ void pin(uint32_t (&d)[N]) {
#pragma unroll
  for (int i = 0; i < N; i++) asm volatile("" : "+r"(d[i])::"memory");
}

__device__ __forceinline__ uint64_t desc(uint32_t lo, uint32_t hi) { return ((uint64_t)hi << 32) | lo; }
constexpr uint32_t DK_LO = 1 << 16, DK_HI = (2048 >> 4) | (2u << 30);
__device__ __forceinline__ constexpr uint32_t dk_step(int k) { return ((k >> 1) * 512 + (k & 1) * 32) >> 4; }
constexpr uint32_t DN_LO = (512 >> 4) << 16, DN_HI = (2048 >> 4) | (2u << 30), DN_STEP = 4096 >> 4;
constexpr uint32_t DW_LO = (16384 >> 4) << 16, DW_HI = (1024 >> 4) | (1u << 30), DW_STEP = 2048 >> 4;

__device__ __forceinline__ constexpr uint32_t da_step(int k) { return ((k >> 2) * 16384 + (k & 3) * 32) >> 4; }

#define R8(a, i) "+f"(a[i]), "+f"(a[i + 1]), "+f"(a[i + 2]), "+f"(a[i + 3]), "+f"(a[i + 4]), "+f"(a[i + 5]), "+f"(a[i + 6]), "+f"(a[i + 7])
#define R64(a) R8(a, 0), R8(a, 8), R8(a, 16), R8(a, 24), R8(a, 32), R8(a, 40), R8(a, 48), R8(a, 56)
#define D64 "{%0,%1,%2,%3,%4,%5,%6,%7,%8,%9,%10,%11,%12,%13,%14,%15,%16,%17,%18,%19,%20,%21,%22,%23,%24,%25,%26,%27,%28,%29,%30,%31," \
            "%32,%33,%34,%35,%36,%37,%38,%39,%40,%41,%42,%43,%44,%45,%46,%47,%48,%49,%50,%51,%52,%53,%54,%55,%56,%57,%58,%59,%60,%61,%62,%63}"
template <int TB>
__device__ __forceinline__ void mma_rs(float (&d)[64], uint32_t a0, uint32_t a1, uint32_t a2, uint32_t a3, uint64_t db, int acc) {
  asm volatile("{\n.reg .pred p;\nsetp.ne.b32 p, %70, 0;\n"
               "wgmma.mma_async.sync.aligned.m64n128k16.f32.bf16.bf16 " D64 ", {%64,%65,%66,%67}, %68, p, 1, 1, %69;\n}\n"
               : R64(d) : "r"(a0), "r"(a1), "r"(a2), "r"(a3), "l"(db), "n"(TB), "r"(acc));
}
__device__ __forceinline__ void mma_rs64(float (&d)[32], uint32_t a0, uint32_t a1, uint32_t a2, uint32_t a3, uint64_t db, int acc) {
  asm volatile("{\n.reg .pred p;\nsetp.ne.b32 p, %37, 0;\n"
               "wgmma.mma_async.sync.aligned.m64n64k16.f32.bf16.bf16 "
               "{%0,%1,%2,%3,%4,%5,%6,%7,%8,%9,%10,%11,%12,%13,%14,%15,%16,%17,%18,%19,%20,%21,%22,%23,%24,%25,%26,%27,%28,%29,%30,%31}"
               ", {%32,%33,%34,%35}, %36, p, 1, 1, 0;\n}\n"
               : R8(d, 0), R8(d, 8), R8(d, 16), R8(d, 24) : "r"(a0), "r"(a1), "r"(a2), "r"(a3), "l"(db), "r"(acc));
}
template <int TB>
__device__ __forceinline__ void mma_ss(float (&d)[64], uint64_t da, uint64_t db, int acc) {
  asm volatile("{\n.reg .pred p;\nsetp.ne.b32 p, %67, 0;\n"
               "wgmma.mma_async.sync.aligned.m64n128k16.f32.bf16.bf16 " D64 ", %64, %65, p, 1, 1, 0, %66;\n}\n"
               : R64(d) : "l"(da), "l"(db), "n"(TB), "r"(acc));
}

__device__ __forceinline__ int split_step(int c) { return (c & 8) ? 7 - 2 * (c & 3) : 9 + 2 * (c & 3); }
__device__ __forceinline__ int item_tile(int c, int n, int rank) { const int t = split_step(c) - 1 + rank; return n ? 15 - t : t; }
__device__ __forceinline__ int p3_head(int i, int kh, int r) {
  return i < 8 ? 2 * i + kh : 16 + 4 * (i & 3) + 2 * (((i >> 2) ^ (r >> 3) ^ 1) & 1) + kh;
}
template <int N> using IC = std::integral_constant<int, N>;
struct Slot {
  int s; uint32_t p;
  __device__ __forceinline__ Slot take() { const Slot r = *this; if (++s == NSLOT - 1) { s = 0; p ^= 1; } return r; }
  __device__ __forceinline__ Slot take7() { const Slot r = *this; if (++s == NSLOT) s = 0; if (s == NSLOT - 1) p ^= 1; return r; }
};

__device__ __forceinline__ void st16(uint8_t* dst, uint32_t a, uint32_t b, uint32_t c, uint32_t d, int keep) {
  asm volatile("{\n.reg .pred p;\nsetp.ne.b32 p, %5, 0;\n@p st.global.v4.u32 [%0], {%1, %2, %3, %4};\n"
               "@!p st.global.cs.v4.u32 [%0], {%1, %2, %3, %4};\n}\n" ::"l"(dst), "r"(a), "r"(b), "r"(c), "r"(d), "r"(keep) : "memory");
}
template <bool SCALE>
__device__ __forceinline__ void store_tile(uint8_t* dst, const float (&a)[64], float s0, float s1, int keep = 1) {
#pragma unroll
  for (int hh = 0; hh < 2; hh++) {
    const float s = SCALE ? (hh ? s1 : s0) : 1.f;
#pragma unroll
    for (int J = 0; J < 4; J++) {
      uint4 v;
      v.x = pack2(a[16 * J + 2 * hh + 0] * s, a[16 * J + 2 * hh + 1] * s);
      v.y = pack2(a[16 * J + 2 * hh + 4] * s, a[16 * J + 2 * hh + 5] * s);
      v.z = pack2(a[16 * J + 2 * hh + 8] * s, a[16 * J + 2 * hh + 9] * s);
      v.w = pack2(a[16 * J + 2 * hh + 12] * s, a[16 * J + 2 * hh + 13] * s);
      st16(dst + hh * 2048 + J * 512, v.x, v.y, v.z, v.w, keep);
    }
  }
}

__device__ __forceinline__ void pack_tile(uint32_t (&v)[32], const float (&a)[64], float s0, float s1) {
#pragma unroll
  for (int i = 0; i < 32; i++) {
    const int b = 4 * (i & 15) + 2 * (i >> 4);
    v[i] = pack2(a[b] * (i < 16 ? s0 : s1), a[b + 1] * (i < 16 ? s0 : s1));
  }
  pin(v);
}

__device__ __forceinline__ void quad_transpose(uint32_t& a0, uint32_t& a1, uint32_t& a2, uint32_t& a3, int t4) {
  const bool od = t4 & 1, hi = t4 & 2;
  const uint32_t e0 = __shfl_xor_sync(0xffffffffu, od ? a0 : a1, 1), e1 = __shfl_xor_sync(0xffffffffu, od ? a2 : a3, 1);
  if (od) { a0 = e0; a2 = e1; } else { a1 = e0; a3 = e1; }
  const uint32_t f0 = __shfl_xor_sync(0xffffffffu, hi ? a0 : a2, 2), f1 = __shfl_xor_sync(0xffffffffu, hi ? a1 : a3, 2);
  if (hi) { a0 = f0; a1 = f1; } else { a2 = f0; a3 = f1; }
}

__device__ __forceinline__ float warp_sum(float v) {
#pragma unroll
  for (int o = 16; o; o >>= 1) v += __shfl_xor_sync(0xffffffffu, v, o);
  return v;
}

__device__ __forceinline__ uint32_t lds32(uint32_t a) { uint32_t v; asm volatile("ld.shared.b32 %0, [%1];" : "=r"(v) : "r"(a) : "memory"); return v; }
__device__ __forceinline__ void side_work(const Params& p, const CUtensorMap* tm_g, const CUtensorMap* tm_u, uint8_t* smem, int q) {
  const int tid = threadIdx.x, warp = __shfl_sync(0xffffffffu, tid >> 5, 0), lane = tid & 31;
  const uint32_t ring = (smem_u32(smem) + 1023) & ~1023u;
  const uint32_t bar_full = ring + NSLOT * TILE, bar_empty = bar_full + 64;
  const uint32_t s_key = bar_full + 128, s_vec = bar_full + 256;
  const unsigned ep = g_epoch[128 + q] + 1;
  if (tid == 32) {
#pragma unroll 1
    for (int i = 0; i < 16; i++) mbar_init(bar_full + 8 * i, i < 8 ? 1 : 8);
    asm volatile("fence.mbarrier_init.release.cluster;" ::: "memory");
  }
  __syncthreads();
  if (tid == 0) g_epoch[128 + q] = ep;
  int x = 0;
  if (warp == 8) {
    uint32_t par = 1;
    __nanosleep(6000);
    flag_wait(&g_flag[F_LN + 32 * q + lane], ep, 200);
    __syncwarp();
    fence_async_global();
#pragma unroll 1
    for (int i = 0; i < 59; i++) {
      mbar_spin(bar_empty + 8 * x, par);
      const uint32_t dst = ring + x * TILE, fb = bar_full + 8 * x;
      if (i < 16) fill_bulk(dst, g_xn + (q * 16 + i) * 32 * DM, fb);
      else if (i < 48) fill_ffn(dst, tm_g, tm_u, fb, q * 172, (i - 16) * 16);
      else fill_stream(dst, p.w_down + (q * 344 + (i - 48) * 32) * DM, fb, i < 58 ? 32768 : 24576);
      __syncwarp();
      if (++x == NSLOT) { x = 0; par ^= 1; }
    }
  } else if (warp < 8) {
    uint32_t par = 0;
    auto open = [&]() { mbar_sleep(bar_full + 8 * x, par); return ring + x * TILE; };
    auto close = [&](float last) {
      __syncwarp();
      mbar_arrive_lt(bar_empty + 8 * x + (__float_as_uint(last) & p.zero), lane, 1);
      __syncwarp();
      if (++x == NSLOT) { x = 0; par ^= 1; }
    };
    unsigned long long key = 0;
    uint32_t w[8];
#pragma unroll
    for (int i = 0; i < 8; i++) w[i] = __ldg(reinterpret_cast<const uint32_t*>(p.w_r) + i * 32 + lane);
#pragma unroll 1
    for (int st = 0; st < 16; st++) {
      const uint32_t base = open() + warp * 4096 + lane * 4;
      float dot;
#pragma unroll 2
      for (int j = 0; j < 4; j++) {
        dot = 0.f;
#pragma unroll
        for (int i = 0; i < 8; i++) { const uint32_t v = lds32(base + j * 1024 + i * 128); dot = fmaf(bf_lo(v), bf_lo(w[i]), fmaf(bf_hi(v), bf_hi(w[i]), dot)); }
        const int row = 512 * q + 32 * st + 4 * warp + j;
        dot = rbf(warp_sum(dot));
        uint32_t u = __float_as_uint(dot);
        u = (u & 0x80000000u) ? ~u : (u | 0x80000000u);
        const unsigned long long k = ((unsigned long long)u << 32) | (unsigned)(SEQ - 1 - row);
        key = k > key ? k : key;
      }
      close(__uint_as_float((uint32_t)key));
    }
    asm volatile("st.shared.b64 [%0], %1;" ::"r"(s_key + 8 * warp), "l"(key) : "memory");
    bar_sync(3, 256);
    if (warp == 0) {
#pragma unroll 1
      for (int i = 1; i < 8; i++) { unsigned long long k; asm volatile("ld.shared.b64 %0, [%1];" : "=l"(k) : "r"(s_key + 8 * i) : "memory"); key = k > key ? k : key; }
      if (lane == 0) { g_key[q] = key; flag_set(&g_flag[F_KEY + q], ep); }
      __syncwarp();
      flag_wait(&g_flag[F_KEY + (lane & 3)], ep);
      __syncwarp();
    }
    bar_sync(3, 256);
#pragma unroll
    for (int i = 0; i < 4; i++) { const unsigned long long k = __ldcg(&g_key[i]); key = k > key ? k : key; }
    const int idx = SEQ - 1 - (int)(key & 0xffffffffu);
    asm volatile("st.shared.b32 [%0], %1;" ::"r"(s_vec + 4 * tid), "r"(__ldcg(reinterpret_cast<const uint32_t*>(g_xn + idx * DM) + tid)) : "memory");
    bar_sync(3, 256);
    float g0 = 0.f, g1 = 0.f, u0 = 0.f, u1 = 0.f;
#pragma unroll 1
    for (int st = 0; st < 32; st++) {
      const uint32_t base = open() + min(tid, 171) * 4;
      if (warp < 6) {
#pragma unroll 4
        for (int k = 0; k < 16; k += 2) {
          const uint32_t xv = lds32(s_vec + st * 32 + k * 2);
          const uint32_t a = lds32(base + k * 688), b = lds32(base + 16384 + k * 688), c = lds32(base + (k + 1) * 688), d = lds32(base + 16384 + (k + 1) * 688);
          g0 = fmaf(bf_hi(xv), bf_lo(c), fmaf(bf_lo(xv), bf_lo(a), g0)); g1 = fmaf(bf_hi(xv), bf_hi(c), fmaf(bf_lo(xv), bf_hi(a), g1));
          u0 = fmaf(bf_hi(xv), bf_lo(d), fmaf(bf_lo(xv), bf_lo(b), u0)); u1 = fmaf(bf_hi(xv), bf_hi(d), fmaf(bf_lo(xv), bf_hi(b), u1));
        }
      }
      close(g0 + u0);
    }
    bar_sync(3, 256);
    g0 = rbf(g0); g1 = rbf(g1);
    asm volatile("st.shared.b32 [%0], %1;" ::"r"(s_vec + 4 * tid),
                 "r"(pack2(rbf(__fdividef(g0, 1.f + __expf(-g0))) * rbf(u0), rbf(__fdividef(g1, 1.f + __expf(-g1))) * rbf(u1))) : "memory");
    bar_sync(3, 256);
    float y0 = 0.f, y1 = 0.f;
#pragma unroll 1
    for (int st = 0; st < 11; st++) {
      const uint32_t base = open() + tid * 4;
#pragma unroll 1
      for (int k0 = 0; k0 < min(32, 344 - 32 * st); k0 += 8)
#pragma unroll
      for (int k = k0; k < k0 + 8; k += 2) {
        const uint32_t hv = lds32(s_vec + st * 64 + k * 2), a = lds32(base + k * 1024), b = lds32(base + k * 1024 + 1024);
        y0 = fmaf(bf_hi(hv), bf_lo(b), fmaf(bf_lo(hv), bf_lo(a), y0)); y1 = fmaf(bf_hi(hv), bf_hi(b), fmaf(bf_lo(hv), bf_hi(a), y1));
      }
      close(y0);
    }
    reinterpret_cast<float2*>(g_ypart + q * DM)[tid] = make_float2(y0, y1);
    bar_sync(3, 256);
    if (warp == 0) {
      if (lane == 0) {
        const uint32_t u = (uint32_t)(key >> 32);
        const float r = __uint_as_float((u & 0x80000000u) ? u & 0x7fffffffu : ~u);
        g_sel[q * 2] = __int_as_float(idx);
        g_sel[q * 2 + 1] = rbf(__fdividef(1.f, 1.f + __expf(-r)));
        flag_set(&g_flag[F_FFN + q], ep);
      }
      __syncwarp();
    }
  }
}

#define LDX "ld.global.cs.nc.v4.u32"
__device__ __forceinline__ void ld_row(uint32_t (&v)[8], const bf16* src, int lane) {
  asm volatile(LDX " {%0, %1, %2, %3}, [%4];" : "=r"(v[0]), "=r"(v[1]), "=r"(v[2]), "=r"(v[3]) : "l"(src + lane * 8));
  asm volatile(LDX " {%0, %1, %2, %3}, [%4];" : "=r"(v[4]), "=r"(v[5]), "=r"(v[6]), "=r"(v[7]) : "l"(src + 256 + lane * 8));
}
__device__ __forceinline__ void ln_row(uint32_t (&v)[8]) {
  float s = 0.f;
#pragma unroll
  for (int i = 0; i < 8; i++) s += bf_lo(v[i]) + bf_hi(v[i]);
  const float mean = warp_sum(s) * (1.f / DM);
  float q = 0.f;
#pragma unroll
  for (int i = 0; i < 8; i++) {
    const float d0 = bf_lo(v[i]) - mean, d1 = bf_hi(v[i]) - mean;
    q = fmaf(d0, d0, fmaf(d1, d1, q));
  }
  const float var = rbf(warp_sum(q) * (1.f / DM));
  const uint32_t nm = pack2(-mean, -mean);
  float den, rc;
  asm("sqrt.approx.ftz.f32 %0, %1;" : "=f"(den) : "f"(rbf(var + 1e-5f)));
  asm("rcp.approx.ftz.f32 %0, %1;" : "=f"(rc) : "f"(rbf(den)));
#pragma unroll
  for (int i = 0; i < 8; i++) {
    const uint32_t d = add2(v[i], nm);
    v[i] = pack2(bf_lo(d) * rc, bf_hi(d) * rc);
  }
}

template <bool BY_SM>
__global__ void __cluster_dims__(2, 1, 1) __launch_bounds__(384, 1)
fused_kernel(const __grid_constant__ Params p,
             const __grid_constant__ CUtensorMap tm_c, const __grid_constant__ CUtensorMap tm_xn,
             const __grid_constant__ CUtensorMap tm_wuk, const __grid_constant__ CUtensorMap tm_wuv,
             const __grid_constant__ CUtensorMap tm_wq, const __grid_constant__ CUtensorMap tm_wo,
             const __grid_constant__ CUtensorMap tm_rx, const __grid_constant__ CUtensorMap tm_rn,
             const __grid_constant__ CUtensorMap tm_g, const __grid_constant__ CUtensorMap tm_u) {
  extern __shared__ uint8_t smem_raw[];
  uint32_t sm = blockIdx.x;
  if (BY_SM) asm volatile("mov.u32 %0, %%smid;" : "=r"(sm));
  const int cb = sm >> 1, rank = blockIdx.x & 1;
  if ((cb >> 1) == 30) { side_work(p, &tm_g, &tm_u, smem_raw, sm - 120); return; }
  const int c7 = ((cb - 32) * 37) >> 8;
  const int c = cb < 32 ? (cb & 7) << 3 | cb >> 3 : cb < 60 ? 8 * (cb - 32) - 55 * c7 + 12 : cb - 58;
  const int vb = 2 * c + rank;

  const uint32_t ring = (smem_u32(smem_raw) + 1023) & ~1023u;
  const uint32_t bar_full = ring + NSLOT * TILE, bar_empty = bar_full + 64;
  const uint32_t bar_done = bar_full + 128;
  const uint32_t bar_sel = bar_full + 120;
  const uint32_t sel_box = bar_full + 288;
  const uint32_t bar_dep = bar_full + 304;
  const uint32_t bar_pf = bar_full + 368;
  const uint32_t upd_box = bar_full + 400;
  const int warp = __shfl_sync(0xffffffffu, threadIdx.x >> 5, 0), lane = threadIdx.x & 31;

  const int j1 = c & 7, r1 = 2 * j1 + rank, g1 = c >> 3;
  const int h2 = c >> 2;
  const int kh = (c >> 2) & 1, nb = c & 3, j3 = c >> 3, r3 = 2 * j3 + rank;
  const int sp = split_step(c);

  if (warp < 8) {
    uint32_t lnx[2][8];
    ld_row(lnx[0], p.x + (vb * 16 + 2 * warp) * DM, lane);
    ld_row(lnx[1], p.x + (vb * 16 + 2 * warp + 1) * DM, lane);
    if (threadIdx.x == 0) asm volatile("prefetch.tensormap [%0];" ::"l"(&tm_c) : "memory");
    if (threadIdx.x == 32) asm volatile("prefetch.tensormap [%0];" ::"l"(&tm_wuk) : "memory");
    __syncwarp();
    asm volatile("barrier.cluster.arrive.relaxed.aligned;" ::: "memory");
    asm volatile("setmaxnreg.inc.sync.aligned.u32 240;");
    const int wg = warp >> 2, wq = warp & 3;
    const int g = lane >> 2, t4 = lane & 3;
    const uint32_t ring_d = (ring & 0x3FFFF) >> 4;
    uint32_t empty_c;
    asm("mapa.shared::cluster.u32 %0, %1, %2;" : "=r"(empty_c) : "r"(bar_empty), "r"(lane & 1));
    auto release = [&](int slot) { mbar_arrive_cluster_lt(empty_c + 8 * slot, lane, 2); };
    auto wait_full = [&](Slot x) { mbar_spin(bar_full + 8 * x.s, x.p); };
    auto signal_done = [&](int i) { __syncwarp(); mbar_arrive_lt(bar_done + 8 * i, lane, 1); __syncwarp(); };
    const uint32_t st_off = (wg * 8 + wq * 2) * 2048 + g * 64 + ((t4 ^ (g >> 1)) << 4);
    uint32_t kv_off = (32 * g1 + r1) * TILE + st_off, ctx_off = h2 * 16 * TILE + st_off;
    asm volatile("" : "+r"(kv_off), "+r"(ctx_off));
    if (wg == 1) bar_arrive(1, 256);
    ln_row(lnx[0]);
    ln_row(lnx[1]);
    uint32_t po[32];
    uint8_t* po_dst = reinterpret_cast<uint8_t*>(p.xn + (vb * 16 + 2 * warp) * DM) + lane * 16;
#pragma unroll
    for (int i = 0; i < 32; i++) po[i] = lnx[(i >> 3) & 1][i & 7];
    asm volatile("barrier.cluster.wait.aligned;" ::: "memory");
    Slot cur{0, 0};

#pragma unroll 1
    for (int rd = 0;; rd++) {
      {
        uint32_t a[128];
        float acc[64];
        auto issue = [&](int sl, auto ST) {
          constexpr int st = decltype(ST)::value;
          const uint32_t lo = (ring_d + sl * (TILE >> 4)) | DW_LO;
          wg_fence();
#pragma unroll
          for (int k = 0; k < 8; k++) {
            const int o = (st * 8 + k) * 4;
            mma_rs<1>(acc, a[o], a[o + 1], a[o + 2], a[o + 3], desc(lo + k * DW_STEP, DW_HI), st | k);
          }
          wg_commit();
        };
        Slot xa, xw;
        auto rows = [&](auto ST) {
          xa = cur.take(); xw = cur.take();
          wait_full(xa);
          const uint32_t base = ring + xa.s * TILE + (warp * 16 + (lane & 7) + ((lane >> 3) & 1) * 8) * 128;
#pragma unroll
          for (int k = 0; k < 8; k++) {
            const int o = (decltype(ST)::value * 8 + k) * 4;
            ldsm4(base + (k >> 2) * 16384 + (((2 * (k & 3) + (lane >> 4)) ^ (lane & 7)) << 4), a[o], a[o + 1], a[o + 2], a[o + 3]);
          }
        };
        auto stage0 = [&](auto ST) {
          constexpr int st = decltype(ST)::value;
          wait_full(xw);
          bar_sync(1 + wg, 256);
          const int sw = xw.s;
          issue(sw, ST);
          bar_arrive(2 - wg, 256);
          release(xa.s);
          if (st < 3) rows(IC<(st + 1) & 3>());
          if (st == 1) {
#pragma unroll
            for (int i = 0; i < 4; i++) st16(po_dst + i * 512, po[4 * i], po[4 * i + 1], po[4 * i + 2], po[4 * i + 3], !rd);
          }
          if (st == 2 && rd) {
#pragma unroll
            for (int i = 4; i < 8; i++) st16(po_dst + i * 512, po[4 * i], po[4 * i + 1], po[4 * i + 2], po[4 * i + 3], 0);
            signal_done(5);
          }
          wg_wait<0>();
          release(sw);
        };
        rows(IC<0>());
        stage0(IC<0>()); stage0(IC<1>()); stage0(IC<2>()); stage0(IC<3>());
#pragma unroll 1
        for (int t = 0;;) {
          pin(acc);
          if (rd) mbar_spin(bar_dep + 8 * (2 + (t >> 1)), 0);
          const uint32_t off = kv_off + (t & 1) * 16 * TILE;
          const float sc = 0.08838834764831845f * 1.4426950408889634f;
          if (t < 2) {
#pragma unroll
            for (int i = 0; i < 64; i++) acc[i] *= sc;
          }
          store_tile<false>((t < 2 ? g_k : g_v) + off, acc, 1.f, 1.f);
          signal_done(6 * rd + t);
          if (++t == 4) break;
          int prev;
          auto stage = [&](auto ST) {
            constexpr int st = decltype(ST)::value;
            const Slot x = cur.take();
            wait_full(x);
            if (st == 0) bar_sync(1 + wg, 256);
            issue(x.s, ST);
            if (st == 3) bar_arrive(2 - wg, 256);
            if (st > 0) { wg_wait<1>(); release(prev); }
            prev = x.s;
          };
          stage(IC<0>()); stage(IC<1>()); stage(IC<2>()); stage(IC<3>());
          wg_wait<0>();
          release(prev);
          __syncwarp();
        }
      }
      uint32_t q[32];
      float s[64], o[64];
      {
#pragma unroll
        for (int kc = 0; kc < 4; kc++) {
          const Slot x0 = cur.take(), xw = cur.take(), x1 = cur.take();
          wait_full(x0);
          wait_full(xw);
          bar_sync(1 + wg, 256);
          const uint32_t a0 = (ring_d + x0.s * (TILE >> 4) + wg * 512) | DK_LO, a1 = (ring_d + x1.s * (TILE >> 4) + (wg ^ 1) * 512) | DK_LO;
          const uint32_t lo = (ring_d + xw.s * (TILE >> 4)) | DW_LO;
          wg_fence();
#pragma unroll
          for (int k = 0; k < 8; k++) mma_ss<1>(s, desc(a0 + da_step(k), DW_HI), desc(lo + k * DW_STEP, DW_HI), kc | k);
          wg_commit();
          wait_full(x1);
          const uint32_t lo2 = lo | p.zero;
          wg_fence();
#pragma unroll
          for (int k = 0; k < 8; k++) mma_ss<1>(o, desc(a1 + da_step(k), DW_HI), desc(lo2 + k * DW_STEP, DW_HI), kc | k);
          wg_commit();
          bar_arrive(2 - wg, 256);
          if (kc == 2) {
#pragma unroll
            for (int i = 0; i < 32; i++) asm volatile("mov.b32 %0, 0;" : "=r"(q[i]));
          }
          wg_wait<1>();
          release(x0.s);
          if (kc == 3 && p.zero == 0) {
            pin(s);
#pragma unroll
            for (int i = 0; i < 32; i++) q[i] = pack2(s[2 * i], s[2 * i + 1]);
#pragma unroll
            for (int i = 0; i < 8; i++) {
              const int b = 8 * (i >> 1) + (i & 1);
              quad_transpose(q[b], q[b + 2], q[b + 4], q[b + 6], t4);
            }
          }
          wg_wait<0>();
          release(xw.s);
          release(x1.s);
        }
        pin(o);
      }

      {
        uint32_t pr[32];
        float m0 = 0.f, m1 = 0.f, l0 = 0.f, l1 = 0.f, t0 = 0.f, t1 = 0.f, u0 = 0.f, u1 = 0.f;
        bool gen;
        int keep = 0;
        const int mthr = wq * 16 + g - 2 * t4;
        const int f1 = sp + rank;
        const int nhalf = f1 - 1 + wg;

        auto issue_qk = [&](int sl) {
          const uint32_t lo = (ring_d + sl * (TILE >> 4)) | DK_LO;
#pragma unroll
          for (int k = 0; k < 8; k++) mma_rs<0>(s, q[4 * k], q[4 * k + 1], q[4 * k + 2], q[4 * k + 3], desc(lo + dk_step(k), DK_HI), k);
        };
        auto issue_qk64 = [&](int sl, float (&h)[32]) {
          const uint32_t lo = (ring_d + sl * (TILE >> 4)) | DK_LO;
#pragma unroll
          for (int k = 0; k < 8; k++) mma_rs64(h, q[4 * k], q[4 * k + 1], q[4 * k + 2], q[4 * k + 3], desc(lo + dk_step(k), DK_HI), k);
        };
        auto issue_pv = [&](int sl, auto NK) {
          const uint32_t lo = (ring_d + sl * (TILE >> 4)) | DN_LO;
#pragma unroll
          for (int k = 0; k < 8; k++) {
            if (k < decltype(NK)::value)
              mma_rs<1>(o, pr[4 * k], pr[4 * k + 1], pr[4 * k + 2], pr[4 * k + 3], desc(lo + k * DN_STEP, DN_HI), k ? 1 : keep);
            if (k == 0 || k == 3 || k == 7) wg_commit();
          }
        };
        auto mask = [&](auto B) {
          constexpr int b = decltype(B)::value;
#pragma unroll
          for (int i = 0; i < 16; i++) {
            const int x = b + 4 * (i >> 1) + (i & 1);
            if (8 * (i >> 1) + (i & 1) > mthr) { s[x] = -INFINITY; if (i < 14) s[x + 6] = -INFINITY; }
          }
          if (b == 0 && mthr < -8) s[2] = s[3] = -INFINITY;
        };
        auto fast = [&](auto J0, auto J1) {
#pragma unroll
          for (int j = decltype(J0)::value; j < decltype(J1)::value; j++) {
            const float e0 = ex2(s[4 * j]), e1 = ex2(s[4 * j + 1]), e2 = ex2(s[4 * j + 2]), e3 = ex2(s[4 * j + 3]);
            if (j == 0) { t0 = e0; u0 = e1; t1 = e2; u1 = e3; } else { t0 += e0; u0 += e1; t1 += e2; u1 += e3; }
            pr[2 * j] = pack2(e0, e1); pr[2 * j + 1] = pack2(e2, e3);
          }
#pragma unroll
          for (int j = decltype(J0)::value; j < decltype(J1)::value; j++) asm volatile("" : "+r"(pr[2 * j]), "+r"(pr[2 * j + 1]));
          asm volatile("" : "+f"(t0), "+f"(t1), "+f"(u0), "+f"(u1));
        };
        auto quad_sum = [&](float v) {
          v += __shfl_xor_sync(0xffffffffu, v, 1);
          return v + __shfl_xor_sync(0xffffffffu, v, 2);
        };
        auto too_big = [&]() {
          t0 += u0; t1 += u1;
          return (bool)__any_sync(0xffffffffu, !(t0 + t1 <= 1.125899906842624e15f));
        };
        auto too_small = [&]() {
          uint32_t b0 = __ballot_sync(0xffffffffu, t0 >= 9.313225746154785e-10f), b1 = __ballot_sync(0xffffffffu, t1 >= 9.313225746154785e-10f);
          b0 |= b0 >> 1; b1 |= b1 >> 1;
          return ((b0 | b0 >> 2) & (b1 | b1 >> 2) & 0x11111111u) != 0x11111111u;
        };
        auto online = [&](bool first) {
          float x0 = fmaxf(s[0], s[1]), x1 = fmaxf(s[2], s[3]);
#pragma unroll
          for (int j = 1; j < 16; j++) {
            x0 = fmaxf(x0, fmaxf(s[4 * j], s[4 * j + 1])); x1 = fmaxf(x1, fmaxf(s[4 * j + 2], s[4 * j + 3]));
          }
          x0 = fmaxf(x0, __shfl_xor_sync(0xffffffffu, x0, 1)); x1 = fmaxf(x1, __shfl_xor_sync(0xffffffffu, x1, 1));
          x0 = fmaxf(x0, __shfl_xor_sync(0xffffffffu, x0, 2)); x1 = fmaxf(x1, __shfl_xor_sync(0xffffffffu, x1, 2));
          if (!first) {
            x0 = fmaxf(x0, m0); x1 = fmaxf(x1, m1);
            const float a0 = ex2(m0 - x0), a1 = ex2(m1 - x1);
            l0 *= a0; l1 *= a1;
#pragma unroll
            for (int j = 0; j < 16; j++) { o[4 * j] *= a0; o[4 * j + 1] *= a0; o[4 * j + 2] *= a1; o[4 * j + 3] *= a1; }
          }
          m0 = x0; m1 = x1;
          t0 = t1 = 0.f;
#pragma unroll
          for (int j = 0; j < 16; j++) {
            const float e0 = ex2(s[4 * j] - x0), e1 = ex2(s[4 * j + 1] - x0), e2 = ex2(s[4 * j + 2] - x1), e3 = ex2(s[4 * j + 3] - x1);
            t0 += e0 + e1; t1 += e2 + e3;
            pr[2 * j] = pack2(e0, e1); pr[2 * j + 1] = pack2(e2, e3);
          }
        };
        auto row_scale = [&]() { l0 = __fdividef(1.f, quad_sum(l0)); l1 = __fdividef(1.f, quad_sum(l1)); };
        auto finish_item = [&](int n) {
          const float r0 = l0, r1_ = l1;
          store_tile<true>(g_ctx + ((ctx_off ^ (n * 16384)) + (256 * rd + (n ? 16 - f1 : f1 - 1)) * TILE), o, r0, r1_, rd);
          signal_done(6 * rd + 4 + n);
        };
        using I0 = IC<0>; using IA = IC<2>; using IB = IC<8>; using I16 = IC<16>;

        Slot ck = cur.take(), cv;
        auto plan = [&](int n) {
          cv = ck = cur.take();
          if (n < NSTEP) cv = cur.take();
        };
        wait_full(ck);
        cv = ck;
        gen = false;
#pragma unroll
        for (int i = 0; i < 32; i++) asm volatile("mov.b32 %0, 0;" : "=r"(pr[i]));
#pragma unroll 1
        for (int n = 0; n < NSTEP; n++) {
          const bool first = n == f1 || n == 0, edge = (unsigned)(f1 - n) < 2u, half = n == nhalf;
          bool okk, okv;
          auto step = [&](auto HQ, auto PV) {
            constexpr bool hq = decltype(HQ)::value;
            constexpr int pv = decltype(PV)::value;
            const int sk = ck.s, sv = cv.s;
            bar_sync(1 + wg, 256);
            wg_fence();
            float h[32];
            if (hq) issue_qk64(sk, h); else issue_qk(sk);
            if (pv) issue_pv(sv, PV); else wg_commit();
            bar_arrive(2 - wg, 256);
            plan(n + 1);
            if (!pv) {
#pragma unroll
              for (int i = 0; i < 8; i++) {
                const int b = 16 * (i & 3) + 2 * (i >> 2);
                asm volatile("st.shared.v4.b32 [%0], {%1, %2, %3, %4};" ::"r"(ring + 6 * TILE + (ctx_off & (TILE - 1)) + i * 512), "r"(pack2(o[b], o[b + 1])),
                             "r"(pack2(o[b + 4], o[b + 5])), "r"(pack2(o[b + 8], o[b + 9])), "r"(pack2(o[b + 12], o[b + 13])) : "memory");
              }
            }
            okk = mbar_test(bar_full + 8 * ck.s, ck.p); okv = mbar_test(bar_full + 8 * cv.s, cv.p);
            gen &= !first;
            keep = !first;
            constexpr bool fin = pv && (hq || pv == 4);
            if (fin && first) release(6);
            if (fin && first) row_scale();
            if (hq) {
#pragma unroll
              for (int i = 32; i < 64; i++) asm volatile("mov.b32 %0, 0xff800000;" : "=f"(s[i]));
            }
            if (n == NSTEP - 1 && rd == 0 && warp == 0)
              asm volatile("{\n.reg .pred p;\n.reg .b32 e, b;\n.reg .b64 a;\nelect.sync _|p, 0xffffffff;\nld.shared.v2.b32 {e, b}, [%1];\n"
                           "mad.wide.u32 a, b, 4, %0;\n@p st.relaxed.gpu.global.u32 [a], e;\n@p mbarrier.arrive.shared::cta.b64 _, [%2];\n}\n"
                           ::"l"(g_flag + F_KR), "r"(sel_box + 8), "r"(bar_done + 8 * 13) : "memory");
            wg_wait<pv ? 2 : 0>();
            if (hq) {
              pin(h);
#pragma unroll
              for (int i = 0; i < 32; i++) s[i] = h[i];
            } else pin(s);
            release(sk);
            if (pv != 4 && n + 1 == f1) {
              __syncwarp();
              const uint32_t base = ring + 6 * TILE + (wg * 8 + wq * 2 + ((lane >> 3) & 1)) * 2048 + (lane & 7) * 64 + (((lane >> 4) ^ ((lane >> 1) & 3)) << 4);
#pragma unroll
              for (int k = 0; k < 8; k++) ldsm4((base + (k >> 1) * 512) ^ ((k & 1) * 32), q[4 * k], q[4 * k + 1], q[4 * k + 2], q[4 * k + 3]);
            }
            if (hq) mask(IC<0>());
            if (!gen) fast(I0(), IA());
            if (pv) wg_wait<1>();
            if (!gen) fast(IA(), IB());
            if (!hq && edge) mask(IC<32>());
            if (pv) {
              wg_wait<0>();
              pin(o);
              release(sv);
            }
            if (fin && first) finish_item(0);
            if (!gen) {
              if (!hq) fast(IB(), I16());
              gen = too_big();
            }
          };
          if (n == 0) { if (half) step(std::true_type(), IC<0>()); else step(std::false_type(), IC<0>()); }
          else if (half) step(std::true_type(), IC<8>());
          else if (n == nhalf + 1) step(std::false_type(), IC<4>());
          else step(std::false_type(), IC<8>());
          if (first | gen | !okk | !okv) {
            if (first) {
              gen |= too_small();
              l0 = l1 = m0 = m1 = 0.f;
            }
            if (gen) online(first);
            if (!(okk & okv)) { wait_full(ck); wait_full(cv); }
            __syncwarp();
          }
          l0 += t0; l1 += t1;
        }
        bar_sync(1 + wg, 256);
        if (nhalf == NSTEP - 1) { wg_fence(); issue_pv(cv.s, IC<4>()); bar_arrive(2 - wg, 256); row_scale(); wg_wait<0>(); }
        else { wg_fence(); issue_pv(cv.s, IC<8>()); bar_arrive(2 - wg, 256); row_scale(); wg_wait<0>(); }
        pin(o);
        release(cv.s);
        if (rd) { finish_item(1); break; }
        pack_tile(po, o, l0, l1);
        po_dst = g_ctx + ((ctx_off ^ 16384) + (16 - f1) * TILE);
      }
    }

    {
      cur.s = NSLOT - 1;
      float acc[64];
#pragma unroll
      for (int i = 0; i < 64; i++) acc[i] = 0.f;
      {
        uint32_t e, b;
        asm volatile("ld.shared.v2.b32 {%0, %1}, [%2];" : "=r"(e), "=r"(b) : "r"(sel_box + 8) : "memory");
        asm volatile("{\n.reg .pred p;\nsetp.ge.u32 p, %2, 24;\n@p st.volatile.global.v4.u32 [%0], {%1, %1, %1, %1};\n}\n"
                     ::"l"(g_part + (b * 8 + warp) * 256 + 7 * 32 + lane), "r"(~e), "r"(lane) : "memory");
      }
      if (wg) {
        const Slot x = cur.take7();
        wait_full(x);
        release(x.s);
        __syncwarp();
      }
#pragma unroll 1
      for (int i = 0;; i++) {
        const Slot x0 = cur.take7(), x1 = cur.take7();
        wait_full(x0);
        wait_full(x1);
        const uint32_t alo = (ring_d + (wg ? x1.s : x0.s) * (TILE >> 4) + wg * 1024) | DK_LO, blo = (ring_d + (wg ? x0.s : x1.s) * (TILE >> 4)) | DW_LO;
        bar_sync(1 + wg, 256);
        wg_fence();
#pragma unroll
        for (int k = 0; k < 8; k++) mma_ss<1>(acc, desc(alo + dk_step(k), DK_HI), desc(blo + k * DW_STEP, DW_HI), 1);
        wg_commit();
        if (wg == 0 || i < 15) bar_arrive(2 - wg, 256);
        if (i == 15) break;
        wg_wait<0>();
        mbar_arrive_cluster_lt(empty_c + 8 * x0.s, lane, i + wg <= 13 ? 2 : 0);
        mbar_arrive_cluster_lt(empty_c + 8 * x1.s, lane, i <= 12 ? 2 : 0);
        __syncwarp();
      }
      mbar_spin(bar_sel, 0);
      uint32_t idx, tag, bid;
      asm volatile("ld.shared.v4.b32 {%0, _, %1, %2}, [%3];" : "=r"(idx), "=r"(tag), "=r"(bid) : "r"(sel_box) : "memory");
      const int kh = (bid >> 3) & 1, nb = (bid >> 1) & 3, r3 = 2 * (bid >> 4) + (bid & 1);
      tag &= 1;
      wg_wait<0>();
      pin(acc);
      uint4* mine = g_part + (bid * 8 + warp) * 256 + lane;
#pragma unroll
      for (int i = 0; i < 8; i++)
        asm volatile("{\n.reg .b64 a, b;\n.reg .b128 w;\nmov.b64 a, {%1, %2};\nmov.b64 b, {%3, %4};\nmov.b128 w, {a, b};\n"
                     "st.relaxed.gpu.global.b128 [%0], w;\n}\n" ::"l"(mine + i * 32), "r"((__float_as_uint(acc[32 + 4 * i]) & ~1u) | tag),
                     "f"(acc[33 + 4 * i]), "f"(acc[34 + 4 * i]), "f"(acc[35 + 4 * i]) : "memory");
      const int row = r3 * 128 + wg * 64 + wq * 16 + g, col = nb * 128 + kh * 64 + t4 * 8;
      uint4 xv[4], nv[4];
      {
        if (wg == 0) cur.take7();
        const Slot x = cur.take7();
        wait_full(x);
        const uint32_t base = ring + x.s * TILE + (row & 127) * 128;
#pragma unroll
        for (int j = 0; j < 4; j++) {
          const uint32_t ad = base + (j >> 1) * 1024 + ((((j & 1) * 4 + t4) ^ g) << 4);
          asm volatile("ld.shared.v4.b32 {%0, %1, %2, %3}, [%4];" : "=r"(xv[j].x), "=r"(xv[j].y), "=r"(xv[j].z), "=r"(xv[j].w) : "r"(ad) : "memory");
          asm volatile("ld.shared.v4.b32 {%0, %1, %2, %3}, [%4];" : "=r"(nv[j].x), "=r"(nv[j].y), "=r"(nv[j].z), "=r"(nv[j].w) : "r"(ad + 16384) : "memory");
        }
        if ((row | 8) == (int)(idx | 8)) {
#pragma unroll
          for (int j = 0; j < 2; j++) {
            uint4 d;
            asm volatile("ld.shared.v4.b32 {%0, %1, %2, %3}, [%4];" : "=r"(d.x), "=r"(d.y), "=r"(d.z), "=r"(d.w) : "r"(upd_box + j * 64 + t4 * 16) : "memory");
            if (idx & 8) nv[2 + j] = make_uint4(add2(nv[2 + j].x, d.x), add2(nv[2 + j].y, d.y), add2(nv[2 + j].z, d.z), add2(nv[2 + j].w, d.w));
            else nv[j] = make_uint4(add2(nv[j].x, d.x), add2(nv[j].y, d.y), add2(nv[j].z, d.z), add2(nv[j].w, d.w));
          }
        }
        __syncwarp();
      }
      const uint4* theirs = g_part + ((bid ^ 8) * 8 + warp) * 256 + lane;
      uint32_t y[32], miss;
      if (lane == 31) {
        while (true) {
          asm volatile("ld.relaxed.gpu.global.u32 %0, [%1];" : "=r"(miss) : "l"(theirs + 7 * 32) : "memory");
          if (!((miss ^ tag) & 1)) break;
          __nanosleep(20);
        }
      }
      __syncwarp();
      do {
#pragma unroll
        for (int i = 0; i < 8; i++)
          asm volatile("{\n.reg .b64 a, b;\n.reg .b128 w;\nld.relaxed.gpu.global.b128 w, [%4];\nmov.b128 {a, b}, w;\n"
                       "mov.b64 {%0, %1}, a;\nmov.b64 {%2, %3}, b;\n}\n"
                       : "=r"(y[4 * i]), "=r"(y[4 * i + 1]), "=r"(y[4 * i + 2]), "=r"(y[4 * i + 3]) : "l"(theirs + i * 32) : "memory");
        miss = 0;
#pragma unroll
        for (int i = 0; i < 8; i++) miss |= y[4 * i] ^ tag;
      } while (__any_sync(0xffffffffu, miss & 1));
      signal_done(12);
      uint32_t u[16];
#pragma unroll
      for (int i = 0; i < 8; i++) {
        u[i] = pack2(acc[4 * i] + __uint_as_float(y[4 * i] & ~1u), acc[4 * i + 1] + __uint_as_float(y[4 * i + 1]));
        u[8 + i] = pack2(acc[4 * i + 2] + __uint_as_float(y[4 * i + 2]), acc[4 * i + 3] + __uint_as_float(y[4 * i + 3]));
      }
#pragma unroll
      for (int i = 0; i < 4; i++) {
        uint32_t a0 = u[4 * i], a1 = u[4 * i + 1], a2 = u[4 * i + 2], a3 = u[4 * i + 3];
        quad_transpose(a0, a1, a2, a3, t4);
        const int rr = row + (i >> 1) * 8, cc = col + (i & 1) * 32;
        *reinterpret_cast<uint4*>(p.out + rr * DM + cc) =
            make_uint4(add2(add2(xv[i].x, a0), nv[i].x), add2(add2(xv[i].y, a1), nv[i].y), add2(add2(xv[i].z, a2), nv[i].z), add2(add2(xv[i].w, a3), nv[i].w));
      }
    }
  } else {
    asm volatile("setmaxnreg.dec.sync.aligned.u32 24;");
    if (warp == 8) {
      if (lane == 0) {
#pragma unroll
        for (int i = 0; i < NSLOT; i++) mbar_init(bar_full + 8 * i, 1);
        asm volatile("fence.mbarrier_init.release.cluster;" ::: "memory");
      }
      __syncwarp();
#pragma unroll 1
      for (int st = 0; st < 3; st++) {
        fill_3d(ring + 2 * st * TILE, &tm_c, bar_full + 16 * st, r1 * 128, 2 * st);
        fill_2x2d(ring + (2 * st + 1) * TILE, &tm_wuk, &tm_wuk, bar_full + 16 * st + 8, g1 * 256, g1 * 256 + 64, st * 128);
      }
    } else if (threadIdx.x == 288) {
#pragma unroll
      for (int i = 0; i < NSLOT; i++) mbar_init(bar_empty + 8 * i, 16);
      mbar_init(bar_pf, 1); mbar_init(bar_pf + 8, 1); mbar_init(bar_pf + 16, 1); mbar_init(bar_sel, 1);
    } else if (threadIdx.x == 320) {
#pragma unroll
      for (int i = 0; i < 8; i++) mbar_init(bar_dep + 8 * i, 1);
#pragma unroll
      for (int i = 10; i < 14; i++) mbar_init(bar_done + 8 * i, i < 13 ? 8 : 1);
    } else if (threadIdx.x == 352) {
#pragma unroll
      for (int i = 0; i < 10; i++) mbar_init(bar_done + 8 * i, 8);
    }
    asm volatile("fence.mbarrier_init.release.cluster;" ::: "memory");
    __syncwarp();
    asm volatile("barrier.cluster.arrive.relaxed.aligned;\nbarrier.cluster.wait.aligned;" ::: "memory");
    if (warp == 8) {
      Slot cur{0, 0};
      uint32_t dst, fb;
      auto grab = [&](Slot x) {
        mbar_spin(bar_empty + 8 * x.s, x.p);
        dst = ring + x.s * TILE; fb = bar_full + 8 * x.s;
      };
      auto acquire = [&]() { grab(cur.take()); };
      auto dep = [&](int i) { mbar_spin(bar_dep + 8 * i, 0); };
      const uint8_t* kb = g_k + (size_t)h2 * 16 * TILE;
      const uint8_t* vbase = g_v + (size_t)h2 * 16 * TILE;
#pragma unroll 1
      for (int rd = 0; rd < 2; rd++) {
#pragma unroll 1
        for (int i = rd ? 0 : 3; i < 16; i++) {
          if (i < 4) { acquire(); fill_3d(dst, &tm_c, fb, r1 * 128, 2 * i); }
          const int col = (16 * rd + 2 * g1 + ((i >> 2) & 1)) * 128;
          const CUtensorMap* tw = i < 8 ? &tm_wuk : &tm_wuv;
          acquire();
          fill_2d_mc(dst + rank * 16384, tw, fb, col + rank * 64, (i & 3) * 128);
          if (i == 7 && rd == 0) mbar_arrive_lt(bar_pf, lane, 1);
          __syncwarp();
        }
        dep(0);
#pragma unroll 1
        for (int kc = 0; kc < 4; kc++) {
          acquire(); fill_3d(dst, &tm_xn, fb, item_tile(c, 0, rank) * 128, 2 * kc);
          acquire(); fill_2d_mc(dst + rank * 16384, &tm_wq, fb, (16 * rd + h2) * 128 + rank * 64, kc * 128);
          acquire(); fill_3d(dst, &tm_xn, fb, item_tile(c, 1, rank) * 128, 2 * kc);
        }
        auto load_kv = [&](const uint8_t* base, int s) {
          acquire();
          if (s == sp) fill_bulk(dst, base + (size_t)(rank ? sp : NSTEP - 1 - sp) * TILE, fb);
          else fill_bulk_mc(dst + rank * 16384, base + (size_t)(s < sp ? s : NSTEP - 1 - s) * TILE + rank * 16384, fb);
        };
        dep(1 + 3 * rd);
        load_kv(kb, 0);
#pragma unroll 1
        for (int n = 1; n < NSTEP; n++) {
          load_kv(kb, n);
          load_kv(vbase, n - 1);
          if (n == (rd ? 10 : 12)) mbar_arrive_lt(bar_pf + 8 + 8 * rd, lane, 1);
          __syncwarp();
        }
        load_kv(vbase, NSTEP - 1);
      }
      const uint8_t* prev = g_ctx;
      cur.s = NSLOT - 1;
#pragma unroll 1
      for (int i = 0; i <= 16; i++) {
        if (i == 0 || i == 8 || i == 12) dep(i ? 4 + (i >> 2) : 5);
        const int h = p3_head(i, kh, r3);
        const uint8_t* src = g_ctx + (size_t)(h * 16 + r3) * TILE;
        grab(cur.take7());
        fill_halves(dst, src, prev + 16384, fb, i < 16, i > 0);
        prev = src;
        if (i < 16) { grab(cur.take7()); fill_2d_mc(dst + rank * 16384, &tm_wo, fb, nb * 128 + ((rank ^ kh) & 1) * 64, h * 128); }
      }
      grab(cur.take7());
      fill_2x2d(dst, &tm_rx, &tm_rn, fb, nb * 128 + kh * 64, nb * 128 + kh * 64, r3 * 128);
    } else {
      unsigned ep;
      if (threadIdx.x == 288) {
        ep = g_epoch[vb] + 1;
        g_epoch[vb] = ep;
        asm volatile("st.shared.v2.b32 [%0], {%1, %2};" ::"r"(sel_box + 8), "r"(ep), "r"(vb) : "memory");
      }
      __syncwarp();
      if (warp != 11) {
        bar_sync(3, 64);
        asm volatile("ld.shared.b32 %0, [%1];" : "=r"(ep) : "r"(sel_box + 8) : "memory");
      }
      if (warp == 9) {
#pragma unroll 1
        for (int i = 0;; i++) {
          mbar_wait(bar_done + 8 * i, 0);
          if (i == 12) break;
          if (lane == 0) {
            const int hb = i < 6 ? 0 : 16, t = i < 6 ? i : i - 6;
            unsigned* f = t < 4 ? &g_flag[F_KV + ((t >> 1) * NH + hb + 2 * g1 + (t & 1)) * 16 + r1] : &g_flag[F_CTX + (hb + h2) * 16 + item_tile(c, t & 1, rank)];
            flag_set(f, ep);
            if (i == 0) asm volatile("st.relaxed.gpu.global.u32 [%0], %1;" ::"l"(&g_flag[F_LN + vb]), "r"(ep) : "memory");
            if (i == 4) {
              uint32_t a, e, b;
              asm("mapa.shared::cluster.u32 %0, %1, %2;" : "=r"(a) : "r"(sel_box + 8), "r"(rank ^ 1));
              asm volatile("ld.volatile.shared::cluster.v2.b32 {%0, %1}, [%2];" : "=r"(e), "=r"(b) : "r"(a) : "memory");
              if (e != ep || b != (uint32_t)(vb ^ 1)) __trap();
            }
          }
          __syncwarp();
        }
      } else if (warp == 10) {
#pragma unroll 1
        for (int k = 0; k < 8; k++) {
          const int l4 = lane & 15;
          int f;
          if (k == 0) f = F_LN + 8 * item_tile(c, l4 >> 3, rank) + (lane & 7);
          else if (k == 1 || k == 4) f = F_KV + ((lane >> 4) * NH + (k & 4) * 4 + h2) * 16 + l4;
          else if (k == 2) f = F_KR + 16 * g1 + l4;
          else if (k == 3) f = F_CTX + (2 * g1 + (l4 >> 3)) * 16 + (c & 8) + (lane & 7);
          else f = F_CTX + p3_head(k == 5 ? lane & 7 : 4 * k - 16 + (lane & 3), kh, r3) * 16 + r3;
          mbar_sleep(bar_done + 8 * ((0xbb99dd31u >> (4 * k)) & 15), 0);
          flag_wait(&g_flag[f], ep);
          __syncwarp();
          fence_async_global();
          mbar_arrive_lt(bar_dep + 8 * k, lane, 1);
          __syncwarp();
          if (k == 5) {
            flag_wait(&g_flag[F_FFN + (lane & 3)], ep, 200);
            __syncwarp();
            const int idx = __float_as_int(__ldcg(&g_sel[0]));
            if ((idx >> 7) == r3) {
              const float rs = __ldcg(&g_sel[1]);
              float y0 = 0.f, y1 = 0.f;
#pragma unroll
              for (int q = 0; q < 4; q++) {
                const float2 y = __ldcg(reinterpret_cast<const float2*>(g_ypart + q * DM + nb * 128 + kh * 64) + lane);
                y0 += y.x; y1 += y.y;
              }
              asm volatile("st.shared.b32 [%0], %1;" ::"r"(upd_box + 4 * lane), "r"(pack2(rbf(y0) * rs, rbf(y1) * rs)) : "memory");
            }
            if (lane == 0) asm volatile("st.shared.b32 [%0], %1;" ::"r"(sel_box), "r"(idx) : "memory");
            __syncwarp();
            if (lane == 0) mbar_arrive(bar_sel);
          }
        }
      } else {
        auto pf_w = [&](const CUtensorMap* tm, int rd) {
          asm volatile("{\n.reg .pred p;\nelect.sync _|p, 0xffffffff;\n@p cp.async.bulk.prefetch.tensor.2d.L2.global [%0, {%1, %2}];\n}\n"
                       ::"l"(tm), "r"(rd * 2048 + g1 * 256 + (r1 >> 2) * 64), "r"((r1 & 3) * 128) : "memory");
        };
        mbar_sleep(bar_pf, 0);
        pf_w(&tm_wuv, 0);
        mbar_sleep(bar_done + 8 * 1, 0);
        pf_w(&tm_wq, 0);
        mbar_sleep(bar_pf + 8, 0);
        prefetch_l2(p.c + vb * 16384, 16384);
        pf_w(&tm_wuk, 1);
        mbar_sleep(bar_done + 8 * 5, 0);
        pf_w(&tm_wuv, 1);
        mbar_sleep(bar_done + 8 * 7, 0);
        prefetch_l2(g_xn + vb * 8192, 16384);
        pf_w(&tm_wq, 1);
        mbar_sleep(bar_pf + 16, 0);
        mbar_sleep(bar_dep + 8 * 5, 0);
#pragma unroll 1
        for (int i = 0; i < 8; i++) {
          const uint8_t* src = i < 2 ? p.wo + (vb * 2 + i) * 16384
                             : i < 6 ? g_ctx + (size_t)(p3_head(2 * nb + (i >> 2), kh, r3) * 16 + r3) * TILE + (i & 1) * 16384
                                     : reinterpret_cast<const uint8_t*>(i == 6 ? p.x : p.xn) + vb * 16384;
          prefetch_l2(src, 16384);
          __nanosleep(700);
        }
      }
    }
  }
}

typedef CUresult (*EncodeFn)(CUtensorMap*, CUtensorMapDataType, cuuint32_t, void*, const cuuint64_t*, const cuuint64_t*,
                             const cuuint32_t*, const cuuint32_t*, CUtensorMapInterleave, CUtensorMapSwizzle,
                             CUtensorMapL2promotion, CUtensorMapFloatOOBfill);

static void make_act_map(EncodeFn enc, CUtensorMap* m, void* ptr) {
  cuuint64_t gd[3] = {64, SEQ, 8}, gs[2] = {DM * 2, 128};
  cuuint32_t bd[3] = {64, 128, 2}, es[3] = {1, 1, 1};
  enc(m, CU_TENSOR_MAP_DATA_TYPE_BFLOAT16, 3, ptr, gd, gs, bd, es, CU_TENSOR_MAP_INTERLEAVE_NONE, CU_TENSOR_MAP_SWIZZLE_128B,
      CU_TENSOR_MAP_L2_PROMOTION_L2_128B, CU_TENSOR_MAP_FLOAT_OOB_FILL_NONE);
}
static void make_w_map(EncodeFn enc, CUtensorMap* m, void* ptr, int rows, int cols) {
  cuuint64_t gd[2] = {(cuuint64_t)cols, (cuuint64_t)rows}, gs[1] = {(cuuint64_t)cols * 2};
  cuuint32_t bd[2] = {64, 128}, es[2] = {1, 1};
  enc(m, CU_TENSOR_MAP_DATA_TYPE_BFLOAT16, 2, ptr, gd, gs, bd, es, CU_TENSOR_MAP_INTERLEAVE_NONE, CU_TENSOR_MAP_SWIZZLE_128B,
      CU_TENSOR_MAP_L2_PROMOTION_L2_128B, CU_TENSOR_MAP_FLOAT_OOB_FILL_NONE);
}

static void make_ffn_map(EncodeFn enc, CUtensorMap* m, void* ptr) {
  cuuint64_t gd[2] = {FF / 2, DM}, gs[1] = {FF * 2};
  cuuint32_t bd[2] = {172, 16}, es[2] = {1, 1};
  enc(m, CU_TENSOR_MAP_DATA_TYPE_UINT32, 2, ptr, gd, gs, bd, es, CU_TENSOR_MAP_INTERLEAVE_NONE, CU_TENSOR_MAP_SWIZZLE_NONE,
      CU_TENSOR_MAP_L2_PROMOTION_NONE, CU_TENSOR_MAP_FLOAT_OOB_FILL_NONE);
}

extern "C" void kernel_launch(void* const* d_in, const int* in_sizes, int n_in, void* d_out, int out_size) {
  (void)in_sizes; (void)n_in; (void)out_size;
  void* fn = nullptr;
  cudaDriverEntryPointQueryResult qr;
  cudaGetDriverEntryPoint("cuTensorMapEncodeTiled", &fn, cudaEnableDefault, &qr);
  EncodeFn enc = (EncodeFn)fn;
  void* xn = nullptr;
  cudaGetSymbolAddress(&xn, g_xn);
  CUtensorMap tm_c, tm_xn, tm_wuk, tm_wuv, tm_wq, tm_wo, tm_rx, tm_rn, tm_g, tm_u;
  make_act_map(enc, &tm_c, d_in[1]);
  make_act_map(enc, &tm_xn, xn);
  make_w_map(enc, &tm_wq, d_in[2], DM, NH * 128);
  make_w_map(enc, &tm_wuk, d_in[3], DM, NH * 128);
  make_w_map(enc, &tm_wuv, d_in[4], DM, NH * 128);
  make_w_map(enc, &tm_wo, d_in[5], NH * 128, DM);
  make_w_map(enc, &tm_rx, d_in[0], SEQ, DM);
  make_w_map(enc, &tm_rn, xn, SEQ, DM);
  make_ffn_map(enc, &tm_g, d_in[8]);
  make_ffn_map(enc, &tm_u, d_in[9]);
  Params p;
  p.x = (const bf16*)d_in[0];
  p.w_r = (const bf16*)d_in[7];
  p.w_down = (const bf16*)d_in[10];
  p.c = (const uint8_t*)d_in[1];
  p.wo = (const uint8_t*)d_in[5];
  p.out = (bf16*)d_out;
  p.zero = 0;
  p.xn = (bf16*)xn;
  int dev = 0, nsm = 0;
  cudaGetDevice(&dev);
  cudaDeviceGetAttribute(&nsm, cudaDevAttrMultiProcessorCount, dev);
  auto kern = nsm == 132 ? fused_kernel<true> : fused_kernel<false>;
  cudaFuncSetAttribute(kern, cudaFuncAttributeMaxDynamicSharedMemorySize, SMEM_BYTES);
  kern<<<132, 384, SMEM_BYTES>>>(p, tm_c, tm_xn, tm_wuk, tm_wuv, tm_wq, tm_wo, tm_rx, tm_rn, tm_g, tm_u);
}
```
